```python
import torch

def _softmax(x, axis=-1):
    return torch.softmax(x, dim=axis)
def _gelu(x):
    return torch.nn.functional.gelu(x, approximate="tanh")
def _silu(x):
    return torch.nn.functional.silu(x)
def _sigmoid(x):
    return torch.sigmoid(x)
def _layernorm(x, axis=-1, eps=1e-5):
    m = x.mean(dim=axis, keepdim=True)
    v = x.var(dim=axis, keepdim=True, unbiased=False)
    return (x - m) / torch.sqrt(v + eps)
def _scatter_add(tgt, idx, src, axis=0):
    return tgt.clone().index_add_(axis, idx, src)
def _segment_sum(src, seg, n):
    out = torch.zeros((n,) + src.shape[1:], dtype=src.dtype)
    return out.index_add_(0, seg, src)
def _pad(x, pw):
    flat = tuple(v for pair in reversed(pw) for v in pair)
    return torch.nn.functional.pad(x, flat)

kernel_name = 'parallel_sum__linear_kernel_hedgehog__dense_activation_gelu__prompt'

def setup_inputs():

    _w = (lambda a: (lambda t: t.to(torch.bfloat16) if t.is_floating_point() else t)(torch.as_tensor(a)))
    def _A_setup():
        B, S, D, H = 1, 2048, 512, 32
        Dh = D // H
        return {
            "x": _w((lambda *s: torch.randn(*s, dtype=torch.bfloat16) * 0.05)(B, S, D)),
            "wqkv": _w((lambda *s: torch.randn(*s, dtype=torch.bfloat16) * 0.2)(D, 3 * D)),
            "w_phi": _w((lambda *s: torch.randn(*s, dtype=torch.bfloat16) * 0.2)(H, Dh, Dh) * (Dh ** -0.5)),
            "wo": _w((lambda *s: torch.randn(*s, dtype=torch.bfloat16) * 0.05)(D, D)),
        }
    _A_in = _A_setup()

    def _B_setup():
        B, S, D, F = 1, 2048, 512, 1376
        return {
            "x": _w((lambda *s: torch.randn(*s, dtype=torch.bfloat16) * 0.05)(B, S, D)),
            "w1": _w((lambda *s: torch.randn(*s, dtype=torch.bfloat16) * 0.8)(D, F) * (D ** -0.5)),
            "b1": _w((lambda *s: torch.randn(*s, dtype=torch.bfloat16) * 12.8)(F) * 0.01),
            "w2": _w((lambda *s: torch.randn(*s, dtype=torch.bfloat16) * 0.4)(F, D) * (F ** -0.5)),
            "b2": _w((lambda *s: torch.randn(*s, dtype=torch.bfloat16) * 6.4)(D) * 0.01),
        }
    _B_in = _B_setup()

    return {
        "A_x": _A_in["x"],
        "A_wqkv": _A_in["wqkv"],
        "A_w_phi": _A_in["w_phi"],
        "A_wo": _A_in["wo"],
        "B_x": _B_in["x"],
        "B_w1": _B_in["w1"],
        "B_b1": _B_in["b1"],
        "B_w2": _B_in["w2"],
        "B_b2": _B_in["b2"],
    }

def reference(A_x, A_wqkv, A_w_phi, A_wo, B_x, B_w1, B_b1, B_w2, B_b2):
    def _A_ref(x, wqkv, w_phi, wo):
        B, S, D = x.shape
        H = 32; Dh = D // H
        qkv = (lambda x, *d: x.permute(*d))((x @ wqkv).reshape(B, S, 3, H, Dh), 2, 0, 3, 1, 4)
        q, k, v = qkv[0], qkv[1], qkv[2]
        pq = torch.einsum("bhsd,hdf->bhsf", q, w_phi)
        pk = torch.einsum("bhsd,hdf->bhsf", k, w_phi)
        phi_q = torch.concatenate([_softmax(pq, axis=-1), _softmax(-pq, axis=-1)], axis=-1)
        phi_k = torch.concatenate([_softmax(pk, axis=-1), _softmax(-pk, axis=-1)], axis=-1)
        kv = torch.einsum("bhsf,bhsd->bhfd", phi_k, v)
        z  = torch.einsum("bhsf->bhf", phi_k)
        num = torch.einsum("bhqf,bhfd->bhqd", phi_q, kv)
        den = torch.einsum("bhqf,bhf->bhq", phi_q, z)[..., None] + 1e-6
        o = num / den
        return (lambda x, *d: x.permute(*d))(o, 0, 2, 1, 3).reshape(B, S, D) @ wo

    def _B_ref(x, w1, b1, w2, b2):
        h = torch.einsum("bsd,df->bsf", x, w1) + b1
        h = _gelu(h)
        return torch.einsum("bsf,fd->bsd", h, w2) + b2

    x = A_x
    xn = _layernorm(x, axis=-1)
    return x + _A_ref(xn, A_wqkv, A_w_phi, A_wo) + _B_ref(xn, B_w1, B_b1, B_w2, B_b2)
```

```cpp
#include <cuda_runtime.h>
#include <cuda.h>
#include <cuda_bf16.h>
#include <stdint.h>

namespace {

constexpr int DM = 512, FF = 1376;
constexpr int NCTA = 128, NTHREADS = 384;

constexpr uint32_t SMEM_BASE = 1024;
constexpr uint32_t REGION = 65536;
constexpr uint32_t OFF_RING = 131072, STAGE = 16384, NST = 6;
constexpr uint32_t OFF_ONES = 229376;
constexpr uint32_t OFF_BAR = 230400;
constexpr uint32_t OFF_B1 = 230656;
constexpr uint32_t OFF_Z = 231424;
constexpr uint32_t OFF_TAG = 232000;
constexpr uint32_t SMEM_BYTES = 232064;
constexpr uint32_t R_PHI = 0, R_V = 16384, R_HOWN = 0, R_HPART = 24576, R_KVP = 55296, R_KVB = 55296, R_OUT = 0;
constexpr uint32_t B_FULL = 0, B_EMPTY = 6, B_HXF = 12, B_HXO = 14, B_RX = 16, B_KVP = 18, B_KVB = 20, B_AUX = 21;
constexpr int KVN = 2176;

constexpr int SPIN_LIMIT = 1 << 22;

}

__device__ __align__(1024) __nv_bfloat16 g_wfold[DM * 1024];
__device__ __align__(1024) float g_kv[8 * KVN];
__device__ __align__(1024) uint4 g_part[NCTA * 3 * 2 * 4 * 128];
__device__ unsigned g_cnt_fold[8 * 32];
__device__ unsigned g_cnt_kv[8 * 32];
__device__ unsigned g_epoch[NCTA * 8];
#define TS(i) do {} while (0)
#define TSL(i) do {} while (0)

namespace {

__device__ __forceinline__ uint32_t smem_u32(const void* p) { return (uint32_t)__cvta_generic_to_shared(p); }
__device__ __forceinline__ void mbar_init(uint32_t b, int c) { asm volatile("mbarrier.init.shared::cta.b64 [%0], %1;" ::"r"(b), "r"(c) : "memory"); }
__device__ __forceinline__ void mbar_expect(uint32_t b, uint32_t tx) { asm volatile("mbarrier.arrive.expect_tx.shared::cta.b64 _, [%0], %1;" ::"r"(b), "r"(tx) : "memory"); }
__device__ __forceinline__ void mbar_arrive(uint32_t b) { asm volatile("mbarrier.arrive.shared::cta.b64 _, [%0];" ::"r"(b) : "memory"); }
#define MBAR_WAIT_BODY(QUAL) \
    "{.reg .pred p; .reg .u32 it;\n" \
    "setp.eq.u32 p, %2, 0;\n" \
    "@p bra.uni DONE;\n" \
    "mov.u32 it, 0;\n" \
    "LOOP:\n" \
    "mbarrier.try_wait.parity" QUAL ".shared::cta.b64 p, [%0], %1;\n" \
    "@p bra DONE;\n" \
    "add.u32 it, it, 1;\n" \
    "setp.lt.u32 p, it, 4194304;\n" \
    "@p bra LOOP;\n" \
    "trap;\n" \
    "DONE:\n}"
__device__ __forceinline__ void mbar_wait(uint32_t b, uint32_t ph, uint32_t cond = 1) {
    asm volatile(MBAR_WAIT_BODY("") ::"r"(b), "r"(ph), "r"(cond) : "memory");
}
__device__ __forceinline__ void mbar_wait_cl(uint32_t b, uint32_t ph) {
    asm volatile(MBAR_WAIT_BODY(".acquire.cluster") ::"r"(b), "r"(ph), "r"(1) : "memory");
}
__device__ __forceinline__ void mbar_arrive_if(uint32_t b, uint32_t cond) {
    asm volatile("{.reg .pred p; setp.ne.u32 p, %1, 0; @p mbarrier.arrive.shared::cta.b64 _, [%0];}" ::"r"(b), "r"(cond) : "memory");
}
__device__ __forceinline__ void sts32f_if(uint32_t a, float x, uint32_t cond) {
    asm volatile("{.reg .pred p; setp.ne.u32 p, %2, 0; @p st.shared.f32 [%0], %1;}" ::"r"(a), "f"(x), "r"(cond) : "memory");
}
__device__ __forceinline__ uint32_t mapa(uint32_t a, uint32_t cta) { uint32_t r; asm("mapa.shared::cluster.u32 %0, %1, %2;" : "=r"(r) : "r"(a), "r"(cta)); return r; }
__device__ __forceinline__ void bar_sync(int id, int n) { asm volatile("bar.sync %0, %1;" ::"r"(id), "r"(n) : "memory"); }
__device__ __forceinline__ void bar_arrive(int id, int n) { asm volatile("bar.arrive %0, %1;" ::"r"(id), "r"(n) : "memory"); }
__device__ __forceinline__ void fence_async_smem() { asm volatile("fence.proxy.async.shared::cta;" ::: "memory"); }
__device__ __forceinline__ void fence_async_all() { asm volatile("fence.proxy.async;" ::: "memory"); }
__device__ __forceinline__ void tma2d(uint32_t dst, const CUtensorMap* m, int c0, int c1, uint32_t bar) {
    asm volatile("cp.async.bulk.tensor.2d.shared::cluster.global.mbarrier::complete_tx::bytes [%0], [%1, {%3, %4}], [%2];"
                 ::"r"(dst), "l"(m), "r"(bar), "r"(c0), "r"(c1) : "memory");
}
__device__ __forceinline__ void poll_counter(const unsigned* p, unsigned target) {
    int it = 0;
    while (true) {
        unsigned v;
        asm volatile("ld.acquire.gpu.global.u32 %0, [%1];" : "=r"(v) : "l"(p) : "memory");
        if ((int)(v - target) >= 0) break;
        if (++it > (SPIN_LIMIT >> 2)) __trap();
    }
}
__device__ __forceinline__ void red_release(unsigned* p) { asm volatile("red.release.gpu.global.add.u32 [%0], 1;" ::"l"(p) : "memory"); }
__device__ __forceinline__ uint32_t pack2(float lo, float hi) { uint32_t r; asm("cvt.rn.bf16x2.f32 %0, %1, %2;" : "=r"(r) : "f"(hi), "f"(lo)); return r; }
__device__ __forceinline__ float bf_lo(uint32_t v) { return __uint_as_float(v << 16); }
__device__ __forceinline__ float bf_hi(uint32_t v) { return __uint_as_float(v & 0xffff0000u); }
__device__ __forceinline__ float ex2f(float x) { float r; asm("ex2.approx.ftz.f32 %0, %1;" : "=f"(r) : "f"(x)); return r; }
__device__ __forceinline__ float rcpf(float x) { float r; asm("rcp.approx.ftz.f32 %0, %1;" : "=f"(r) : "f"(x)); return r; }
__device__ __forceinline__ float tanhf_(float x) { float r; asm("tanh.approx.f32 %0, %1;" : "=f"(r) : "f"(x)); return r; }
__device__ __forceinline__ void sts128(uint32_t a, uint32_t x, uint32_t y, uint32_t z, uint32_t w) { asm volatile("st.shared.v4.b32 [%0], {%1,%2,%3,%4};" ::"r"(a), "r"(x), "r"(y), "r"(z), "r"(w) : "memory"); }
__device__ __forceinline__ void sts64f(uint32_t a, float x, float y) { asm volatile("st.shared.v2.f32 [%0], {%1,%2};" ::"r"(a), "f"(x), "f"(y) : "memory"); }
__device__ __forceinline__ void sts32f(uint32_t a, float x) { asm volatile("st.shared.f32 [%0], %1;" ::"r"(a), "f"(x) : "memory"); }
__device__ __forceinline__ void lds128(uint32_t a, uint32_t* r) { asm volatile("ld.shared.v4.b32 {%0,%1,%2,%3}, [%4];" : "=r"(r[0]), "=r"(r[1]), "=r"(r[2]), "=r"(r[3]) : "r"(a) : "memory"); }
__device__ __forceinline__ void lds128f(uint32_t a, float* r) { asm volatile("ld.shared.v4.f32 {%0,%1,%2,%3}, [%4];" : "=f"(r[0]), "=f"(r[1]), "=f"(r[2]), "=f"(r[3]) : "r"(a) : "memory"); }
__device__ __forceinline__ void lds64f(uint32_t a, float& x, float& y) { asm volatile("ld.shared.v2.f32 {%0,%1}, [%2];" : "=f"(x), "=f"(y) : "r"(a) : "memory"); }
__device__ __forceinline__ void st_async128(uint32_t a, uint32_t x, uint32_t y, uint32_t z, uint32_t w, uint32_t bar) {
    asm volatile("st.async.weak.shared::cluster.mbarrier::complete_tx::bytes.v4.b32 [%0], {%1,%2,%3,%4}, [%5];" ::"r"(a), "r"(x), "r"(y), "r"(z), "r"(w), "r"(bar) : "memory");
}
__device__ __forceinline__ void ldsm4(uint32_t a, uint32_t* r) { asm volatile("ldmatrix.sync.aligned.m8n8.x4.shared.b16 {%0,%1,%2,%3}, [%4];" : "=r"(r[0]), "=r"(r[1]), "=r"(r[2]), "=r"(r[3]) : "r"(a) : "memory"); }
__device__ __forceinline__ void stsm4(uint32_t a, uint32_t x, uint32_t y, uint32_t z, uint32_t w) { asm volatile("stmatrix.sync.aligned.m8n8.x4.shared.b16 [%0], {%1,%2,%3,%4};" ::"r"(a), "r"(x), "r"(y), "r"(z), "r"(w) : "memory"); }
__device__ __forceinline__ uint32_t ldg32(const void* p) { uint32_t r; asm volatile("ld.global.nc.b32 %0, [%1];" : "=r"(r) : "l"(p)); return r; }
__device__ __forceinline__ uint32_t ldg16(const void* p) { uint16_t r; asm volatile("ld.global.nc.b16 %0, [%1];" : "=h"(r) : "l"(p)); return r; }
__device__ __forceinline__ void ld_poll128(const uint4* p, uint32_t* r) { asm volatile("ld.relaxed.gpu.global.v4.b32 {%0,%1,%2,%3}, [%4];" : "=r"(r[0]), "=r"(r[1]), "=r"(r[2]), "=r"(r[3]) : "l"(p) : "memory"); }
__device__ __forceinline__ void st_rel128(uint4* p, uint32_t x, uint32_t y, uint32_t z, uint32_t w) { asm volatile("st.relaxed.gpu.global.v4.b32 [%0], {%1,%2,%3,%4};" ::"l"(p), "r"(x), "r"(y), "r"(z), "r"(w) : "memory"); }
__device__ __forceinline__ void mma16816(float* c, const uint32_t* a, uint32_t b0, uint32_t b1) {
    asm volatile("mma.sync.aligned.m16n8k16.row.col.f32.bf16.bf16.f32 {%0,%1,%2,%3}, {%4,%5,%6,%7}, {%8,%9}, {%10,%10,%10,%10};"
                 : "=f"(c[0]), "=f"(c[1]), "=f"(c[2]), "=f"(c[3]) : "r"(a[0]), "r"(a[1]), "r"(a[2]), "r"(a[3]), "r"(b0), "r"(b1), "f"(0.f));
}

__device__ __forceinline__ void wg_fence() { asm volatile("wgmma.fence.sync.aligned;" ::: "memory"); }
__device__ __forceinline__ void wg_commit() { asm volatile("wgmma.commit_group.sync.aligned;" ::: "memory"); }
template <int N> __device__ __forceinline__ void wg_wait() { asm volatile("wgmma.wait_group.sync.aligned %0;" ::"n"(N) : "memory"); }
template <int N> __device__ __forceinline__ void reg_fence(float* d) {
#pragma unroll
    for (int i = 0; i < N; i++) asm volatile("" : "+f"(d[i])::"memory");
}
__device__ __forceinline__ uint64_t desc128(uint32_t addr) { return (uint64_t)((addr & 0x3FFFF) >> 4) | (1ull << 16) | (64ull << 32) | (1ull << 62); }

#define ACC8(d, o) "+f"(d[o + 0]), "+f"(d[o + 1]), "+f"(d[o + 2]), "+f"(d[o + 3]), "+f"(d[o + 4]), "+f"(d[o + 5]), "+f"(d[o + 6]), "+f"(d[o + 7])
template <int SC, uint32_t DLO>
__device__ __forceinline__ void wgmma_rs64(float* d, const uint32_t* a, uint32_t off) {
    asm volatile("{.reg .pred p; .reg .b32 lo; .reg .b64 db; setp.ne.b32 p, %37, 0; add.u32 lo, %36, %38; mov.b64 db, {lo, 0x40000040};\n"
                 "wgmma.mma_async.sync.aligned.m64n64k16.f32.bf16.bf16 "
                 "{%0,%1,%2,%3,%4,%5,%6,%7,%8,%9,%10,%11,%12,%13,%14,%15,%16,%17,%18,%19,%20,%21,%22,%23,%24,%25,%26,%27,%28,%29,%30,%31}, "
                 "{%32,%33,%34,%35}, db, p, 1, 1, 1;}\n"
                 : ACC8(d, 0), ACC8(d, 8), ACC8(d, 16), ACC8(d, 24)
                 : "r"(a[0]), "r"(a[1]), "r"(a[2]), "r"(a[3]), "r"(off), "n"(SC), "n"(DLO));
}
template <int SC, uint32_t DLO>
__device__ __forceinline__ void wgmma_rs48(float* d, const uint32_t* a, uint32_t off) {
    asm volatile("{.reg .pred p; .reg .b32 lo; .reg .b64 db; setp.ne.b32 p, %29, 0; add.u32 lo, %28, %30; mov.b64 db, {lo, 0x40000040};\n"
                 "wgmma.mma_async.sync.aligned.m64n48k16.f32.bf16.bf16 "
                 "{%0,%1,%2,%3,%4,%5,%6,%7,%8,%9,%10,%11,%12,%13,%14,%15,%16,%17,%18,%19,%20,%21,%22,%23}, "
                 "{%24,%25,%26,%27}, db, p, 1, 1, 1;}\n"
                 : ACC8(d, 0), ACC8(d, 8), ACC8(d, 16)
                 : "r"(a[0]), "r"(a[1]), "r"(a[2]), "r"(a[3]), "r"(off), "n"(SC), "n"(DLO));
}
template <int SC>
__device__ __forceinline__ void wgmma_ss40(float* d, uint64_t da, uint64_t db) {
    asm volatile("{.reg .pred p; setp.ne.b32 p, %22, 0;\n"
                 "wgmma.mma_async.sync.aligned.m64n40k16.f32.bf16.bf16 "
                 "{%0,%1,%2,%3,%4,%5,%6,%7,%8,%9,%10,%11,%12,%13,%14,%15,%16,%17,%18,%19}, "
                 "%20, %21, p, 1, 1, 1, 1;}\n"
                 : ACC8(d, 0), ACC8(d, 8), "+f"(d[16]), "+f"(d[17]), "+f"(d[18]), "+f"(d[19])
                 : "l"(da), "l"(db), "n"(SC));
}

struct Ctx {
    uint32_t sb;
    uint32_t R;
    int wg, wq, lane, tid;
};

__device__ __forceinline__ uint32_t bar_addr(uint32_t sb, uint32_t i) { return sb + OFF_BAR + i * 8; }
template <int G> __device__ __forceinline__ void wait_full(const Ctx& c) { mbar_wait(bar_addr(c.sb, B_FULL + G % NST), (G / NST) & 1, c.wg == 0); }
template <int G> __device__ __forceinline__ void release1(const Ctx& c) { mbar_arrive_if(bar_addr(c.sb, B_EMPTY + G % NST), c.wg == 1 && c.lane == 0); }
template <int G0, int NLAST> __device__ __forceinline__ void release_end(const Ctx& c) {
    int s = G0 % NST + (c.lane & 3);
    if (s >= (int)NST) s -= NST;
    mbar_arrive_if(bar_addr(c.sb, B_EMPTY + s), c.lane < 4 && (c.wg == 0 || c.lane >= 4 - NLAST));
}
__host__ __device__ constexpr uint32_t stage_off(int G) { return OFF_RING + (G % NST) * STAGE; }
template <int SLOT> __device__ __forceinline__ void slot_begin(const Ctx& c) {
    wait_full<SLOT * 4>(c); wait_full<SLOT * 4 + 1>(c);
    if (SLOT > 0 || c.wg == 1) bar_sync(1 + c.wg, 256);
}
template <int SLOT> __device__ __forceinline__ void slot_handoff(const Ctx& c) {
    if (SLOT < 9 || c.wg == 0) bar_arrive(1 + (c.wg ^ 1), 256);
}

template <int N, int NK, bool FIRST, uint32_t SOFF, int K = 0>
__device__ __forceinline__ void mma_group(float* acc, const uint32_t* a, uint32_t off = 0) {
    if constexpr (K == 0) wg_fence();
    if constexpr (K < NK) {
        constexpr uint32_t DLO = ((SMEM_BASE + SOFF + K * 2048) >> 4) | (1u << 16);
        constexpr int SC = (FIRST && K == 0) ? 0 : 1;
        if constexpr (N == 64) wgmma_rs64<SC, DLO>(acc, a + 4 * K, off); else wgmma_rs48<SC, DLO>(acc, a + 4 * K, off);
        mma_group<N, NK, FIRST, SOFF, K + 1>(acc, a, off);
    }
}

template <int SLOT, int N>
__device__ __forceinline__ void slot1_rest(const Ctx& c, float* acc, const uint32_t* xa) {
    constexpr int G = SLOT * 4;
    mma_group<N, 8, false, stage_off(G + 1)>(acc, xa + 32);
    wg_commit();
    wait_full<G + 2>(c);
    wg_wait<1>(); release1<G>(c);
    mma_group<N, 8, false, stage_off(G + 2)>(acc, xa + 64);
    wg_commit();
    wait_full<G + 3>(c);
    wg_wait<1>(); release1<G + 1>(c);
    mma_group<N, 8, false, stage_off(G + 3)>(acc, xa + 96);
    wg_commit();
    slot_handoff<SLOT>(c);
    wg_wait<1>(); release1<G + 2>(c);
    wg_wait<0>();
    reg_fence<N / 2>(acc);
    release_end<G, 1>(c);
}
template <int SLOT, int N>
__device__ __forceinline__ void slot1(const Ctx& c, float* acc, const uint32_t* xa) {
    slot_begin<SLOT>(c);
    mma_group<N, 8, true, stage_off(SLOT * 4)>(acc, xa);
    wg_commit();
    slot1_rest<SLOT, N>(c, acc, xa);
}

template <int NV, int VEC0>
__device__ __forceinline__ void epi_gelu(const Ctx& c, const float* acc, float rs0, float rs1, uint32_t rem_h, uint32_t rem_bar) {
    const int t = c.lane & 3;
    const uint32_t bb = c.sb + OFF_B1 + (VEC0 * 16 + 2 * t) * 4;
#pragma unroll
    for (int v = 0; v < NV; v++) {
        uint32_t o[4];
#pragma unroll
        for (int j = 0; j < 2; j++) {
            float b0, b1;
            lds64f(bb + (v * 16 + j * 8) * 4, b0, b1);
            float h[4];
#pragma unroll
            for (int e = 0; e < 4; e++) {
                float u = fmaf(acc[8 * v + 4 * j + e], (e < 2) ? rs0 : rs1, (e & 1) ? b1 : b0);
                float w = u * fmaf(u * u, 0.0356774081363001f, 0.7978845608028654f);
                float hu = 0.5f * u;
                h[e] = fmaf(hu, tanhf_(w), hu);
            }
            o[2 * j] = pack2(h[0], h[1]);
            o[2 * j + 1] = pack2(h[2], h[3]);
        }
        sts128(c.R + R_HOWN + (VEC0 + v) * 2048 + c.tid * 16, o[0], o[1], o[2], o[3]);
        st_async128(rem_h + (VEC0 + v) * 2048, o[0], o[1], o[2], o[3], rem_bar);
    }
}

__device__ __forceinline__ void dual_exp(const float* acc, int ro, float cs, float* ep, float* en, float& sp, float& sn) {
    float mx = fmaxf(acc[ro], acc[ro + 1]), mn = fminf(acc[ro], acc[ro + 1]);
#pragma unroll
    for (int i = 1; i < 8; i++) {
        mx = fmaxf(mx, fmaxf(acc[4 * i + ro], acc[4 * i + ro + 1]));
        mn = fminf(mn, fminf(acc[4 * i + ro], acc[4 * i + ro + 1]));
    }
    const float mxc = -mx * cs, mnc = mn * cs;
    float sp0 = 0.f, sp1 = 0.f, sn0 = 0.f, sn1 = 0.f;
#pragma unroll
    for (int i = 0; i < 8; i++) {
        ep[2 * i] = ex2f(fmaf(acc[4 * i + ro], cs, mxc));
        ep[2 * i + 1] = ex2f(fmaf(acc[4 * i + ro + 1], cs, mxc));
        en[2 * i] = ex2f(fmaf(acc[4 * i + ro], -cs, mnc));
        en[2 * i + 1] = ex2f(fmaf(acc[4 * i + ro + 1], -cs, mnc));
        sp0 += ep[2 * i]; sp1 += ep[2 * i + 1];
        sn0 += en[2 * i]; sn1 += en[2 * i + 1];
    }
    sp = sp0 + sp1; sn = sn0 + sn1;
}

__device__ __forceinline__ void add_packed(float* base, const uint32_t* v) {
#pragma unroll
    for (int j = 0; j < 16; j++) { base[2 * j] += bf_lo(v[j]); base[2 * j + 1] += bf_hi(v[j]); }
}
__device__ __forceinline__ void poll_partial(const uint4* p, uint32_t* v, uint32_t tag, bool preloaded) {
    int it = 0;
    while (true) {
        if (!preloaded) {
#pragma unroll
            for (int j = 0; j < 4; j++) ld_poll128(p + j * 128, v + 4 * j);
        }
        preloaded = false;
        uint32_t bad = ((v[0] ^ tag) | (v[4] ^ tag) | (v[8] ^ tag) | (v[12] ^ tag)) & 1u;
        if (!bad) break;
        if (++it > (SPIN_LIMIT >> 2)) __trap();
    }
}

template <int SLOT, bool LAST>
__device__ __forceinline__ void slot2(const Ctx& c, float* acc, const uint32_t* hf, const uint32_t* of, const uint32_t* pf, uint32_t rank,
                                      const uint4* lastp, uint32_t* lastv) {
    constexpr int G = SLOT * 4;
    slot_begin<SLOT>(c);
    mma_group<64, 8, true, stage_off(G)>(acc, hf);
    wg_commit();
    mma_group<64, 8, false, stage_off(G + 1)>(acc, hf + 32);
    wg_commit();
    wait_full<G + 2>(c);
    wg_wait<1>(); release1<G>(c);
    if (LAST) {
#pragma unroll
        for (int j = 0; j < 4; j++) ld_poll128(lastp + j * 128, lastv + 4 * j);
    }
    mma_group<64, 6, false, stage_off(G + 2)>(acc, hf + 64);
    wg_commit();
    wait_full<G + 3>(c);
    wg_wait<1>(); release1<G + 1>(c);
    mma_group<64, 4, false, stage_off(G + 3)>(acc, of, rank * 512);
    mma_group<64, 4, false, stage_off(G + 3)>(acc, pf, (rank ^ 1) * 512);
    wg_commit();
    slot_handoff<SLOT>(c);
    if (!LAST) {
        wg_wait<1>(); release1<G + 2>(c);
        wg_wait<0>();
        reg_fence<32>(acc);
        release_end<G, 1>(c);
    }
}

__device__ __forceinline__ void send_partial(const float* acc, uint4* dst, uint32_t tag) {
#pragma unroll
    for (int v = 0; v < 4; v++) {
        uint32_t x = pack2(acc[8 * v], acc[8 * v + 1]);
        x = (x & ~1u) | tag;
        st_rel128(dst + v * 128, x, pack2(acc[8 * v + 2], acc[8 * v + 3]), pack2(acc[8 * v + 4], acc[8 * v + 5]), pack2(acc[8 * v + 6], acc[8 * v + 7]));
    }
}

}

__global__ void __launch_bounds__(NTHREADS, 1)
fused_hedgehog_gelu_kernel(const __grid_constant__ CUtensorMap tm_wqkv, const __grid_constant__ CUtensorMap tm_wfold,
                           const __grid_constant__ CUtensorMap tm_w1, const __grid_constant__ CUtensorMap tm_w2,
                           const __grid_constant__ CUtensorMap tm_wo,
                           const __nv_bfloat16* __restrict__ x, const __nv_bfloat16* __restrict__ wqkv,
                           const __nv_bfloat16* __restrict__ wphi, const __nv_bfloat16* __restrict__ wo,
                           const __nv_bfloat16* __restrict__ w1, const __nv_bfloat16* __restrict__ b1,
                           const __nv_bfloat16* __restrict__ w2, const __nv_bfloat16* __restrict__ b2,
                           __nv_bfloat16* __restrict__ out) {
    extern __shared__ __align__(1024) uint8_t smem_raw[];
    const uint32_t sb = smem_u32(smem_raw);
    const int warp = __shfl_sync(0xffffffffu, threadIdx.x >> 5, 0), lane = threadIdx.x & 31;
    const int bid = blockIdx.x, rb = bid >> 3, cs = bid & 7, pr = cs >> 1;
    const uint32_t rank = cs & 1;

    if (warp < 8) {
        asm volatile("setmaxnreg.inc.sync.aligned.u32 232;");
        Ctx c;
        c.sb = sb; c.wg = warp >> 2; c.wq = warp & 3; c.lane = lane; c.tid = threadIdx.x & 127;
        c.R = sb + c.wg * REGION;
        const int g = lane >> 2, t = lane & 3;
        const int row0 = rb * 128 + c.wg * 64 + c.wq * 16;
        TS(0);

        uint32_t fa[32], fb[8];
        const int fm = c.wq >> 1, fn = c.wq & 1;
        if (c.wg == 1) {
            const __nv_bfloat16* wr = wqkv + (size_t)(rb * 32 + fm * 16 + g) * 1536 + cs * 64 + 2 * t;
#pragma unroll
            for (int m = 1; m >= 0; m--)
#pragma unroll
                for (int h = 0; h < 4; h++) {
                    fa[m * 16 + h * 4 + 0] = ldg32(wr + m * 512 + h * 16);
                    fa[m * 16 + h * 4 + 1] = ldg32(wr + m * 512 + h * 16 + 8 * 1536);
                    fa[m * 16 + h * 4 + 2] = ldg32(wr + m * 512 + h * 16 + 8);
                    fa[m * 16 + h * 4 + 3] = ldg32(wr + m * 512 + h * 16 + 8 * 1536 + 8);
                }
            const __nv_bfloat16* wp = wphi + (cs * 4) * 256 + (2 * t) * 16 + fn * 8 + g;
#pragma unroll
            for (int h = 0; h < 4; h++) {
                fb[2 * h] = ldg16(wp + h * 256) | (ldg16(wp + h * 256 + 16) << 16);
                fb[2 * h + 1] = ldg16(wp + h * 256 + 128) | (ldg16(wp + h * 256 + 144) << 16);
            }
        }
        const uint32_t xs = c.R + c.wq * 16384;
        {
            const int r2 = lane >> 4, ch = lane & 15;
            const __nv_bfloat16* xp = x + (size_t)(row0 + r2) * DM + ch * 8;
#pragma unroll
            for (int q = 0; q < 4; q++) {
#pragma unroll
                for (int j = 0; j < 8; j++) {
                    const int r = 2 * j + r2;
                    asm volatile("cp.async.cg.shared.global [%0], [%1], 16;" ::"r"(xs + r * 1024 + q * 256 + ((ch ^ (r & 7)) << 4)),
                                 "l"(xp + (size_t)j * 2 * DM + q * 128) : "memory");
                }
                asm volatile("cp.async.commit_group;" ::: "memory");
            }
        }
        bar_sync(0, NTHREADS);
        asm volatile("barrier.cluster.arrive.relaxed.aligned;" ::: "memory");

        if (c.wg == 1) {
            __nv_bfloat16* wo_ = g_wfold + (size_t)(rb * 32 + fm * 16 + g) * 1024 + cs * 64 + (fn * 4 + t) * 8;
#pragma unroll
            for (int m = 1; m >= 0; m--) {
                uint32_t lo[4], hi[4];
#pragma unroll
                for (int h = 0; h < 4; h++) {
                    float d[4];
                    mma16816(d, fa + m * 16 + h * 4, fb[2 * h], fb[2 * h + 1]);
                    lo[h] = pack2(d[0], d[1]); hi[h] = pack2(d[2], d[3]);
                }
                *(uint4*)(wo_ + m * 512) = make_uint4(lo[0], lo[1], lo[2], lo[3]);
                *(uint4*)(wo_ + m * 512 + 8 * 1024) = make_uint4(hi[0], hi[1], hi[2], hi[3]);
            }
            if (c.tid < KVN / 64) *(float4*)(g_kv + cs * KVN + rb * (KVN / 16) + c.tid * 4) = make_float4(0.f, 0.f, 0.f, 0.f);
            bar_arrive(5, 160);
        }
        TS(1);

        uint32_t xa[128];
        float rs0, rs1;
        {
            float s0 = 0.f, s1 = 0.f, q0 = 0.f, q1 = 0.f, s0b = 0.f, s1b = 0.f, q0b = 0.f, q1b = 0.f;
            const int lr = (lane & 7) + ((lane >> 3) & 1) * 8, lc = lane >> 4;
            const uint32_t la = xs + lr * 1024;
#pragma unroll
            for (int q = 0; q < 4; q++) {
                if (q == 0) asm volatile("cp.async.wait_group 3;" ::: "memory");
                if (q == 1) asm volatile("cp.async.wait_group 2;" ::: "memory");
                if (q == 2) asm volatile("cp.async.wait_group 1;" ::: "memory");
                if (q == 3) asm volatile("cp.async.wait_group 0;" ::: "memory");
                __syncwarp();
#pragma unroll
                for (int k = 0; k < 8; k++) ldsm4(la + q * 256 + (((2 * k + lc) ^ (lr & 7)) << 4), xa + (q * 8 + k) * 4);
#pragma unroll
                for (int k = 0; k < 8; k++) {
                    const uint32_t* r = xa + (q * 8 + k) * 4;
                    float a, b;
                    a = bf_lo(r[0]); b = bf_hi(r[0]); s0 += a; s0b += b; q0 = fmaf(a, a, q0); q0b = fmaf(b, b, q0b);
                    a = bf_lo(r[1]); b = bf_hi(r[1]); s1 += a; s1b += b; q1 = fmaf(a, a, q1); q1b = fmaf(b, b, q1b);
                    a = bf_lo(r[2]); b = bf_hi(r[2]); s0 += a; s0b += b; q0 = fmaf(a, a, q0); q0b = fmaf(b, b, q0b);
                    a = bf_lo(r[3]); b = bf_hi(r[3]); s1 += a; s1b += b; q1 = fmaf(a, a, q1); q1b = fmaf(b, b, q1b);
                }
            }
            s0 += s0b; s1 += s1b; q0 += q0b; q1 += q1b;
#pragma unroll
            for (int o = 1; o <= 2; o <<= 1) {
                s0 += __shfl_xor_sync(0xffffffffu, s0, o); s1 += __shfl_xor_sync(0xffffffffu, s1, o);
                q0 += __shfl_xor_sync(0xffffffffu, q0, o); q1 += __shfl_xor_sync(0xffffffffu, q1, o);
            }
            const float m0 = s0 * (1.f / DM), m1 = s1 * (1.f / DM);
            rs0 = rsqrtf(fmaxf(fmaf(-m0, m0, q0 * (1.f / DM)), 0.f) + 1e-5f);
            rs1 = rsqrtf(fmaxf(fmaf(-m1, m1, q1 * (1.f / DM)), 0.f) + 1e-5f);
            const uint32_t mm0 = pack2(m0, m0), mm1 = pack2(m1, m1);
#pragma unroll
            for (int i = 0; i < 128; i++) asm("sub.rn.bf16x2 %0, %0, %1;" : "+r"(xa[i]) : "r"((i & 1) ? mm1 : mm0));
        }
        bar_sync(3 + c.wg, 128);
        TS(2);

        float acc[32];
        slot1<0, 64>(c, acc, xa);
        TS(3);
        asm volatile("barrier.cluster.wait.aligned;" ::: "memory");
        if (c.tid == 0) {
            asm volatile("fence.release.sync_restrict::shared::cta.cluster;" ::: "memory");
            asm volatile("mbarrier.arrive.relaxed.cluster.shared::cluster.b64 _, [%0];" ::"r"(mapa(bar_addr(sb, B_RX + c.wg), rank ^ 1)) : "memory");
        }
        {
            const int r = c.wq * 16 + (lane & 7) + ((lane >> 3) & 1) * 8;
            const uint32_t va = c.R + R_V + r * 64;
#pragma unroll
            for (int v = 0; v < 4; v++) {
                const int ch = (2 * v + (lane >> 4)) & 3;
                stsm4(va + (v >> 1) * 4096 + ((ch ^ ((r >> 1) & 3)) << 4),
                      pack2(acc[8 * v] * rs0, acc[8 * v + 1] * rs0), pack2(acc[8 * v + 2] * rs1, acc[8 * v + 3] * rs1),
                      pack2(acc[8 * v + 4] * rs0, acc[8 * v + 5] * rs0), pack2(acc[8 * v + 6] * rs1, acc[8 * v + 7] * rs1));
            }
        }
        TS(4);
        slot1<1, 64>(c, acc, xa);
        TS(5);
        const float LOG2E = 1.4426950408889634f;
#pragma unroll
        for (int rr = 0; rr < 2; rr++) {
            float ep[16], en[16], sp, sn;
            dual_exp(acc, 2 * rr, (rr ? rs1 : rs0) * LOG2E, ep, en, sp, sn);
            const float r = rcpf(sp * sn), rp = r * sn, rn = r * sp;
            const int row = c.wq * 16 + g + 8 * rr;
            const uint32_t pa = c.R + R_PHI + (t >> 1) * 8192 + row * 128;
            const int c0 = (t & 1) * 4;
#pragma unroll
            for (int i = 0; i < 2; i++) {
                sts128(pa + (((c0 + i) ^ g) << 4), pack2(ep[8 * i] * rp, ep[8 * i + 1] * rp), pack2(ep[8 * i + 2] * rp, ep[8 * i + 3] * rp),
                       pack2(ep[8 * i + 4] * rp, ep[8 * i + 5] * rp), pack2(ep[8 * i + 6] * rp, ep[8 * i + 7] * rp));
                sts128(pa + (((c0 + 2 + i) ^ g) << 4), pack2(en[8 * i] * rn, en[8 * i + 1] * rn), pack2(en[8 * i + 2] * rn, en[8 * i + 3] * rn),
                       pack2(en[8 * i + 4] * rn, en[8 * i + 5] * rn), pack2(en[8 * i + 6] * rn, en[8 * i + 7] * rn));
            }
        }
        fence_async_smem();
        mbar_wait(bar_addr(sb, B_AUX), 0);
        TS(6);
        const uint32_t rem_h = mapa(c.R + R_HPART + c.tid * 16, rank ^ 1);
        const uint32_t rem_hxf = mapa(bar_addr(sb, B_HXF + c.wg), rank ^ 1);
        {
            float kva[40];
            slot_begin<2>(c);
            wg_fence();
#pragma unroll
            for (int b = 0; b < 2; b++)
#pragma unroll
                for (int s = 0; s < 4; s++) {
                    const uint64_t da = desc128(c.R + R_PHI + b * 8192 + s * 2048);
                    const uint32_t bs = c.R + R_V + b * 4096 + s * 1024;
                    const uint64_t db = (uint64_t)((bs & 0x3FFFF) >> 4) | ((uint64_t)((sb + OFF_ONES - bs) >> 4) << 16) | (32ull << 32) | (2ull << 62);
                    if (s == 0) wgmma_ss40<0>(kva + 20 * b, da, db); else wgmma_ss40<1>(kva + 20 * b, da, db);
                }
            wg_commit();
            mma_group<64, 8, true, stage_off(8)>(acc, xa);
            wg_commit();
            wg_wait<1>();
            reg_fence<40>(kva);
            const bool hi = (c.wq >> 1) != 0;
#pragma unroll
            for (int b = 0; b < 2; b++) {
                const int hs = (2 * b + (c.wq >> 1)) * 2 + (c.wq & 1);
                const uint32_t ka = c.R + R_KVP + (hs * 16 + g) * 64 + t * 8;
                const float* k = kva + 20 * b;
                sts64f(ka, hi ? k[8] : k[0], hi ? k[9] : k[1]);
                sts64f(ka + 512, hi ? k[10] : k[2], hi ? k[11] : k[3]);
                sts64f(ka + 32, hi ? k[12] : k[4], hi ? k[13] : k[5]);
                sts64f(ka + 544, hi ? k[14] : k[6], hi ? k[15] : k[7]);
                sts32f_if(c.R + R_KVP + 8192 + (hs * 16 + g + 8 * (t & 1)) * 4, (t & 1) ? k[18] : k[16], t < 2);
            }
            fence_async_smem();
            mbar_arrive(bar_addr(sb, B_KVP + c.wg));
            slot1_rest<2, 64>(c, acc, xa);
        }
        TS(7);
        bar_sync(3 + c.wg, 128);
        mbar_wait_cl(bar_addr(sb, B_RX + c.wg), 0);
        epi_gelu<4, 0>(c, acc, rs0, rs1, rem_h, rem_hxf);
        TS(8);
        slot1<3, 48>(c, acc, xa);
        TS(9);
        epi_gelu<3, 8>(c, acc, rs0, rs1, rem_h, rem_hxf);
        TS(10);
        slot1<4, 64>(c, acc, xa);
        TS(11);
        epi_gelu<4, 4>(c, acc, rs0, rs1, rem_h, rem_hxf);
        TS(12);
        slot1<5, 64>(c, acc, xa);
        TS(13);
        uint32_t hf[88], qf[32];
        {
            const uint32_t own = c.R + R_HOWN + c.tid * 16, par = c.R + R_HPART + c.tid * 16;
            const uint32_t a0 = rank ? par : own, a1 = rank ? own : par;
            mbar_wait_cl(bar_addr(sb, B_HXF + c.wg), 0);
#pragma unroll
            for (int v = 0; v < 11; v++) { lds128(a0 + v * 2048, hf + 4 * v); lds128(a1 + v * 2048, hf + 44 + 4 * v); }
            float ep0[16], en0[16], ep1[16], en1[16], sp0, sn0, sp1, sn1;
            dual_exp(acc, 0, rs0 * LOG2E, ep0, en0, sp0, sn0);
            dual_exp(acc, 2, rs1 * LOG2E, ep1, en1, sp1, sn1);
            TS(14);
            mbar_wait(bar_addr(sb, B_KVB), 0);
            TS(15);
            float dp0 = 0.f, dn0 = 0.f, dp1 = 0.f, dn1 = 0.f;
#pragma unroll
            for (int i = 0; i < 4; i++) {
                float zp[4], zn[4];
                lds128f(sb + OFF_Z + t * 144 + i * 16, zp);
                lds128f(sb + OFF_Z + t * 144 + 64 + i * 16, zn);
#pragma unroll
                for (int e = 0; e < 4; e++) {
                    dp0 = fmaf(ep0[4 * i + e], zp[e], dp0); dn0 = fmaf(en0[4 * i + e], zn[e], dn0);
                    dp1 = fmaf(ep1[4 * i + e], zp[e], dp1); dn1 = fmaf(en1[4 * i + e], zn[e], dn1);
                }
            }
            const float r0 = rcpf(fmaf(dp0, sn0, fmaf(dn0, sp0, 1e-6f * sp0 * sn0)));
            const float r1 = rcpf(fmaf(dp1, sn1, fmaf(dn1, sp1, 1e-6f * sp1 * sn1)));
            const float ap0 = sn0 * r0, an0 = sp0 * r0, ap1 = sn1 * r1, an1 = sp1 * r1;
#pragma unroll
            for (int i = 0; i < 8; i++) {
                qf[2 * i] = pack2(ep0[2 * i] * ap0, ep0[2 * i + 1] * ap0);
                qf[2 * i + 1] = pack2(ep1[2 * i] * ap1, ep1[2 * i + 1] * ap1);
                qf[16 + 2 * i] = pack2(en0[2 * i] * an0, en0[2 * i + 1] * an0);
                qf[16 + 2 * i + 1] = pack2(en1[2 * i] * an1, en1[2 * i + 1] * an1);
            }
        }
        uint32_t tag;
        asm volatile("ld.shared.b32 %0, [%1];" : "=r"(tag) : "r"(sb + OFF_TAG) : "memory");
        TS(16);
        uint32_t of[16], pf[16];
        {
            float oa[32];
            slot_begin<6>(c);
            mma_group<64, 4, true, R_KVB>(oa, qf);
            mma_group<64, 4, false, REGION + R_KVB>(oa, qf + 16);
            wg_commit();
            mma_group<64, 8, true, stage_off(24)>(acc, hf);
            wg_commit();
            wg_wait<1>();
            reg_fence<32>(oa);
            const uint32_t rem_hxo = mapa(bar_addr(sb, B_HXO + c.wg), rank ^ 1);
#pragma unroll
            for (int j = 0; j < 16; j++) of[j] = pack2(oa[2 * j], oa[2 * j + 1]);
#pragma unroll
            for (int v = 0; v < 4; v++) st_async128(rem_h + (11 + v) * 2048, of[4 * v], of[4 * v + 1], of[4 * v + 2], of[4 * v + 3], rem_hxo);
            mma_group<64, 8, false, stage_off(25)>(acc, hf + 32);
            wg_commit();
            wait_full<26>(c);
            wg_wait<1>(); release1<24>(c);
            mma_group<64, 6, false, stage_off(26)>(acc, hf + 64);
            wg_commit();
            wait_full<27>(c);
            wg_wait<1>(); release1<25>(c);
            mma_group<64, 4, false, stage_off(27)>(acc, of, rank * 512);
            wg_commit();
            slot_handoff<6>(c);
            mbar_wait_cl(bar_addr(sb, B_HXO + c.wg), 0);
#pragma unroll
            for (int v = 0; v < 4; v++) lds128(c.R + R_HPART + (11 + v) * 2048 + c.tid * 16, pf + 4 * v);
            mma_group<64, 4, false, stage_off(27)>(acc, pf, (rank ^ 1) * 512);
            wg_commit();
            wg_wait<0>();
            reg_fence<32>(acc);
            release_end<24, 2>(c);
        }
        TS(17);
        const int grp = (bid & ~7) | (int)rank;
        send_partial(acc, g_part + ((size_t)((grp + 2 * ((pr + 1) & 3)) * 3 + 0) * 2 + c.wg) * 512 + c.tid, tag);
        TS(18);
        slot2<7, false>(c, acc, hf, of, pf, rank, nullptr, nullptr);
        TS(19);
        send_partial(acc, g_part + ((size_t)((grp + 2 * ((pr + 2) & 3)) * 3 + 1) * 2 + c.wg) * 512 + c.tid, tag);
        TS(20);
        slot2<8, false>(c, acc, hf, of, pf, rank, nullptr, nullptr);
        TS(21);
        send_partial(acc, g_part + ((size_t)((grp + 2 * ((pr + 3) & 3)) * 3 + 2) * 2 + c.wg) * 512 + c.tid, tag);
        const int col0 = rank * 256 + pr * 64;
        float base[32];
        uint32_t pv[16];
        const uint4* myp = g_part + ((size_t)bid * 3 * 2 + c.wg) * 512 + c.tid;
        {
            const __nv_bfloat16* xr = x + (size_t)(row0 + g) * DM + col0 + 2 * t;
            uint32_t xv[16], bv[8];
#pragma unroll
            for (int j = 0; j < 4; j++) ld_poll128(myp + j * 128, pv + 4 * j);
#pragma unroll
            for (int j = 0; j < 16; j++) xv[j] = ldg32(xr + (j & 1) * 8 * DM + (j >> 1) * 8);
#pragma unroll
            for (int j = 0; j < 8; j++) bv[j] = ldg32(b2 + col0 + 2 * t + j * 8);
#pragma unroll
            for (int j = 0; j < 16; j++) { base[2 * j] = bf_lo(xv[j]) + bf_lo(bv[j >> 1]); base[2 * j + 1] = bf_hi(xv[j]) + bf_hi(bv[j >> 1]); }
            uint32_t pw[16];
#pragma unroll
            for (int j = 0; j < 4; j++) ld_poll128(myp + 1024 + j * 128, pw + 4 * j);
            poll_partial(myp, pv, tag, true);
            add_packed(base, pv);
            poll_partial(myp + 1024, pw, tag, true);
            add_packed(base, pw);
        }
        TS(22);
        slot2<9, true>(c, acc, hf, of, pf, rank, myp + 2048, pv);
        poll_partial(myp + 2048, pv, tag, true);
        add_packed(base, pv);
        TS(23);
        wg_wait<0>();
        reg_fence<32>(acc);
        TS(24);
        {
            const uint32_t oa = c.R + R_OUT + c.wq * 2048;
            const int r = (lane & 7) + ((lane >> 3) & 1) * 8;
#pragma unroll
            for (int v = 0; v < 4; v++) {
                const int ch = 2 * v + (lane >> 4);
                stsm4(oa + r * 128 + ((ch ^ (r & 7)) << 4),
                      pack2(acc[8 * v] + base[8 * v], acc[8 * v + 1] + base[8 * v + 1]), pack2(acc[8 * v + 2] + base[8 * v + 2], acc[8 * v + 3] + base[8 * v + 3]),
                      pack2(acc[8 * v + 4] + base[8 * v + 4], acc[8 * v + 5] + base[8 * v + 5]), pack2(acc[8 * v + 6] + base[8 * v + 6], acc[8 * v + 7] + base[8 * v + 7]));
            }
            __syncwarp();
#pragma unroll
            for (int j = 0; j < 4; j++) {
                const int rr = 4 * j + (lane >> 3), ch = lane & 7;
                uint32_t v[4];
                lds128(oa + rr * 128 + ((ch ^ (rr & 7)) << 4), v);
                *(uint4*)(out + (size_t)(row0 + rr) * DM + col0 + ch * 8) = make_uint4(v[0], v[1], v[2], v[3]);
            }
        }
        TS(25);
    } else {
        asm volatile("setmaxnreg.dec.sync.aligned.u32 40;");
        unsigned epoch;
        asm volatile("ld.relaxed.gpu.global.u32 %0, [%1];" : "=r"(epoch) : "l"(g_epoch + bid * 8) : "memory");
        if (warp == 8 && lane == 0) {
            asm volatile("prefetch.tensormap [%0];" ::"l"(&tm_wqkv) : "memory");
            if ((sb & 0x3FFFF) != SMEM_BASE) __trap();
#pragma unroll
            for (int i = 0; i < (int)NST; i++) { mbar_init(bar_addr(sb, B_FULL + i), 1); mbar_init(bar_addr(sb, B_EMPTY + i), 8); }
#pragma unroll
            for (int i = 0; i < 2; i++) {
                mbar_init(bar_addr(sb, B_HXF + i), 1); mbar_init(bar_addr(sb, B_HXO + i), 1);
                mbar_init(bar_addr(sb, B_RX + i), 1); mbar_init(bar_addr(sb, B_KVP + i), 128);
            }
            mbar_init(bar_addr(sb, B_KVB), 96);
            mbar_init(bar_addr(sb, B_AUX), 64);
#pragma unroll
            for (int i = 0; i < 2; i++) { mbar_expect(bar_addr(sb, B_HXF + i), 11 * 2048); mbar_expect(bar_addr(sb, B_HXO + i), 4 * 2048); }
            asm volatile("fence.mbarrier_init.release.cluster;" ::: "memory");
            asm volatile("fence.release.sync_restrict::shared::cta.cluster;" ::: "memory");
        }
        __syncwarp();
        bar_sync(0, NTHREADS);
        asm volatile("barrier.cluster.arrive.relaxed.aligned;" ::: "memory");

        if (warp == 8) {
            if (lane == 0) {
                asm volatile("prefetch.tensormap [%0];" ::"l"(&tm_wfold) : "memory");
                asm volatile("prefetch.tensormap [%0];" ::"l"(&tm_w1) : "memory");
                asm volatile("prefetch.tensormap [%0];" ::"l"(&tm_w2) : "memory");
                asm volatile("prefetch.tensormap [%0];" ::"l"(&tm_wo) : "memory");
                int st = 0, ph = 1;
#pragma unroll 1
                for (int gi = 0; gi < 40; gi++) {
                    const int ch = gi >> 2, s = gi & 3;
                    const CUtensorMap* m;
                    int c0, c1 = s * 128;
                    if (ch == 0) { m = &tm_wqkv; c0 = 1024 + cs * 64; }
                    else if (ch == 1) { m = &tm_wfold; c0 = 512 + cs * 64; }
                    else if (ch < 5) { m = &tm_w1; c0 = cs * 176 + (ch == 2 ? 0 : ch == 3 ? 128 : 64); }
                    else if (ch == 5) { m = &tm_wfold; c0 = cs * 64; }
                    else {
                        c0 = rank * 256 + ((pr + ch - 5) & 3) * 64;
                        if (s < 3) { m = &tm_w2; c1 += pr * 352; } else { m = &tm_wo; c1 = pr * 128; }
                    }
                    if (gi == 4) { TSL(0); poll_counter(g_cnt_fold + cs * 32, (epoch + 1) * 16); fence_async_all(); TSL(1); }
                    if (gi >= (int)NST) mbar_wait(bar_addr(sb, B_EMPTY + st), ph);
                    mbar_expect(bar_addr(sb, B_FULL + st), STAGE);
                    tma2d(sb + OFF_RING + st * STAGE, m, c0, c1, bar_addr(sb, B_FULL + st));
                    TSL(16 + gi);
                    if (++st == (int)NST) { st = 0; ph ^= 1; }
                }
            }
        } else {
            const int ht = threadIdx.x - 288;
            if (warp == 9) {
                bar_sync(5, 160);
                if (lane == 0) {
                    red_release(g_cnt_fold + cs * 32);
                    TSL(2);
                    poll_counter(g_cnt_fold + cs * 32, (epoch + 1) * 16);
                    fence_async_all();
#pragma unroll 1
                    for (int w = 0; w < 2; w++) {
                        mbar_wait(bar_addr(sb, B_KVP + w), 0);
                        asm volatile("cp.reduce.async.bulk.global.shared::cta.bulk_group.add.f32 [%0], [%1], %2;"
                                     ::"l"(g_kv + cs * KVN), "r"(sb + w * REGION + R_KVP), "r"(KVN * 4) : "memory");
                        asm volatile("cp.async.bulk.commit_group;" ::: "memory");
                    }
                    TSL(3);
                    asm volatile("cp.async.bulk.wait_group 0;" ::: "memory");
                    fence_async_all();
                    red_release(g_cnt_kv + cs * 32);
                    TSL(4);
                }
                __syncwarp();
            } else {
                const int u = ht - 32;
                float bv[3];
#pragma unroll
                for (int j = 0; j < 3; j++) {
                    const int col = u + 64 * j, gc = cs * 176 + col;
                    bv[j] = (col < 176 && gc < FF) ? __bfloat162float(b1[gc]) : 0.f;
                }
                sts128(sb + OFF_ONES + u * 16, 0x3f803f80u, 0x3f803f80u, 0x3f803f80u, 0x3f803f80u);
#pragma unroll
                for (int j = 0; j < 3; j++) sts32f(sb + OFF_B1 + (u + 64 * j) * 4, bv[j]);
                fence_async_smem();
                mbar_arrive(bar_addr(sb, B_AUX));
                if (u < 3) {
                    mbar_wait(bar_addr(sb, B_FULL), 0);
                    const char* p = (u == 0) ? (const char*)w1 + (size_t)bid * 11008 : (u == 1) ? (const char*)w2 + (size_t)bid * 11008 : (const char*)wo + (size_t)bid * 4096;
                    asm volatile("cp.async.bulk.prefetch.L2.global [%0], %1;" ::"l"(p), "r"(u == 2 ? 4096 : 11008) : "memory");
                }
                __syncwarp();
            }
            bar_sync(6, 96);
#pragma unroll 1
            for (int i = ht; i < 1024; i += 96) sts128(sb + (i >> 9) * REGION + R_KVB + (i & 511) * 16, 0u, 0u, 0u, 0u);
            if (lane == 0) poll_counter(g_cnt_kv + cs * 32, (epoch + 1) * 16);
            bar_sync(6, 96);
            if (ht == 0) TSL(5);
            const float* kvp = g_kv + cs * KVN;
            float4 ld[6];
#pragma unroll
            for (int j = 0; j < 3; j++) {
                const int u = ht + 96 * j;
                if (u < 256) {
                    const int k = u >> 1, sg = k >> 6, f = ((k >> 3) & 7) * 2 + (k & 1), hd = (k >> 1) & 3;
                    const float4* s = (const float4*)(kvp + ((hd * 2 + sg) * 16 + f) * 16 + (u & 1) * 8);
                    ld[2 * j] = __ldcg(s); ld[2 * j + 1] = __ldcg(s + 1);
                } else {
                    ld[2 * j] = __ldcg((const float4*)(kvp + 2048) + lane);
                }
            }
#pragma unroll
            for (int j = 0; j < 3; j++) {
                const int u = ht + 96 * j;
                if (u < 256) {
                    const int k = u >> 1, hd = (k >> 1) & 3;
                    sts128(sb + (k >> 6) * REGION + R_KVB + (k & 63) * 128 + (((2 * hd + (u & 1)) ^ (k & 7)) << 4),
                           pack2(ld[2 * j].x, ld[2 * j].y), pack2(ld[2 * j].z, ld[2 * j].w),
                           pack2(ld[2 * j + 1].x, ld[2 * j + 1].y), pack2(ld[2 * j + 1].z, ld[2 * j + 1].w));
                } else {
                    sts128(sb + OFF_Z + (lane >> 3) * 144 + (lane & 7) * 16, __float_as_uint(ld[2 * j].x), __float_as_uint(ld[2 * j].y),
                           __float_as_uint(ld[2 * j].z), __float_as_uint(ld[2 * j].w));
                }
            }
            if (ht == 0) {
                asm volatile("st.shared.b32 [%0], %1;" ::"r"(sb + OFF_TAG), "r"((epoch + 1) & 1u) : "memory");
                asm volatile("st.relaxed.gpu.global.u32 [%0], %1;" ::"l"(g_epoch + bid * 8), "r"(epoch + 1) : "memory");
            }
            fence_async_smem();
            mbar_arrive(bar_addr(sb, B_KVB));
            if (ht == 0) TSL(6);
        }
    }
}

typedef CUresult (*EncodeFn)(CUtensorMap*, CUtensorMapDataType, cuuint32_t, void*, const cuuint64_t*, const cuuint64_t*,
                             const cuuint32_t*, const cuuint32_t*, CUtensorMapInterleave, CUtensorMapSwizzle,
                             CUtensorMapL2promotion, CUtensorMapFloatOOBfill);

static void make_map(EncodeFn enc, CUtensorMap* m, const void* p, int cols, int rows) {
    cuuint64_t gd[2] = {(cuuint64_t)cols, (cuuint64_t)rows};
    cuuint64_t gs[1] = {(cuuint64_t)cols * 2};
    cuuint32_t bx[2] = {64, 128};
    cuuint32_t es[2] = {1, 1};
    enc(m, CU_TENSOR_MAP_DATA_TYPE_BFLOAT16, 2, const_cast<void*>(p), gd, gs, bx, es, CU_TENSOR_MAP_INTERLEAVE_NONE,
        CU_TENSOR_MAP_SWIZZLE_128B, CU_TENSOR_MAP_L2_PROMOTION_L2_128B, CU_TENSOR_MAP_FLOAT_OOB_FILL_NONE);
}

extern "C" void kernel_launch(void* const* d_in, const int* in_sizes, int n_in, void* d_out, int out_size) {
    const __nv_bfloat16* x = (const __nv_bfloat16*)d_in[0];
    const __nv_bfloat16* wqkv = (const __nv_bfloat16*)d_in[1];
    const __nv_bfloat16* wphi = (const __nv_bfloat16*)d_in[2];
    const __nv_bfloat16* wo = (const __nv_bfloat16*)d_in[3];
    const __nv_bfloat16* w1 = (const __nv_bfloat16*)d_in[5];
    const __nv_bfloat16* b1 = (const __nv_bfloat16*)d_in[6];
    const __nv_bfloat16* w2 = (const __nv_bfloat16*)d_in[7];
    const __nv_bfloat16* b2 = (const __nv_bfloat16*)d_in[8];

    static EncodeFn enc = nullptr;
    static void* wfold = nullptr;
    if (!enc) {
        void* fn = nullptr;
        cudaDriverEntryPointQueryResult qr;
        cudaGetDriverEntryPoint("cuTensorMapEncodeTiled", &fn, cudaEnableDefault, &qr);
        enc = (EncodeFn)fn;
        cudaGetSymbolAddress(&wfold, g_wfold);
        cudaFuncSetAttribute(fused_hedgehog_gelu_kernel, cudaFuncAttributeMaxDynamicSharedMemorySize, SMEM_BYTES);
    }
    CUtensorMap m_wqkv, m_wfold, m_w1, m_w2, m_wo;
    make_map(enc, &m_wqkv, wqkv, 1536, DM);
    make_map(enc, &m_wfold, wfold, 1024, DM);
    make_map(enc, &m_w1, w1, FF, DM);
    make_map(enc, &m_w2, w2, DM, FF);
    make_map(enc, &m_wo, wo, DM, DM);

    cudaLaunchConfig_t cfg = {};
    cfg.gridDim = dim3(NCTA);
    cfg.blockDim = dim3(NTHREADS);
    cfg.dynamicSmemBytes = SMEM_BYTES;
    cfg.stream = cudaStreamPerThread;
    cudaLaunchAttribute at[1];
    at[0].id = cudaLaunchAttributeClusterDimension;
    at[0].val.clusterDim.x = 2; at[0].val.clusterDim.y = 1; at[0].val.clusterDim.z = 1;
    cfg.attrs = at; cfg.numAttrs = 1;
    cudaLaunchKernelEx(&cfg, fused_hedgehog_gelu_kernel, m_wqkv, m_wfold, m_w1, m_w2, m_wo, x, wqkv, wphi, wo, w1, b1, w2, b2,
                       (__nv_bfloat16*)d_out);
}
```

```cpp
#include <cuda_runtime.h>
#include <cuda.h>
#include <cuda_bf16.h>
#include <stdint.h>

namespace {

constexpr int DM = 512, FF = 1376;
constexpr int NCTA = 128, NTHREADS = 384;

constexpr uint32_t SMEM_BASE = 1024;
constexpr uint32_t OFF_RING = 0;
constexpr uint32_t OFF_X = 98304;
constexpr uint32_t RSTEP = 49152;
constexpr uint32_t OFF_KVB = 131072;
constexpr uint32_t OFF_REG = 133120;
constexpr uint32_t R_PHI = 0;
constexpr uint32_t R_HPF = 16384;
constexpr uint32_t R_HPO = 38912;
constexpr uint32_t OFF_BPHI = OFF_REG + RSTEP + R_HPF, OFF_FIN = OFF_BPHI + 16384, OFF_FOUT = OFF_REG + R_HPF + 16384;
constexpr uint32_t OFF_XR = OFF_BPHI;
constexpr uint32_t OFF_ONES = 229376;
constexpr uint32_t OFF_B1 = 231424;
constexpr uint32_t OFF_BAR = 232128;
constexpr uint32_t SMEM_BYTES = 232448;
constexpr uint32_t B_FULL = 0, B_EMPTY = 4, B_HXF = 8, B_HXG = 10, B_HXO = 12, B_RX = 14, B_KVP = 16, B_KVB = 17, B_AUX = 18, B_XD = 19, B_TAG = 20, B_XR = 21, B_XD0 = 22, B_BPHI = 23;
constexpr uint32_t B_X = 24, B_V = 32;
constexpr uint32_t B_FI = 34, B_FO = 35, B_RXG = 36, B_HD0 = 37;
constexpr int KVN = 3072;
#define BOUNDED 0

struct SlotDesc {
    uint64_t d[10];
    uint64_t r[2][4][4];
    uint64_t bphi, kva[4], kvb[4], fa, fb, oa[2], ob;
};

constexpr int SPIN_LIMIT = 1 << 22;

}

__device__ __align__(1024) uint4 g_wfold[8 * 4096];
__device__ __align__(1024) float g_kv[8 * KVN];
__device__ __align__(1024) uint4 g_part[NCTA * 3 * 2 * 4 * 128];
__device__ unsigned g_cnt_fold[8 * 32];
__device__ unsigned g_cnt_zero[8 * 32];
__device__ unsigned g_epoch[NCTA * 8];
#define TSA() do {} while (0)
#define TSB() do {} while (0)
#define TSR() do {} while (0)
#define TSR2() do {} while (0)
#define TSW2(i) do {} while (0)
#define TSW(i) do {} while (0)
#define TSG(i) do {} while (0)
#define TS(i) do {} while (0)
#define TSL(i) do {} while (0)

namespace {

__device__ __forceinline__ uint32_t smem_u32(const void* p) { return (uint32_t)__cvta_generic_to_shared(p); }
__device__ __forceinline__ void mbar_init(uint32_t b, int c) { asm volatile("mbarrier.init.shared::cta.b64 [%0], %1;" ::"r"(b), "r"(c) : "memory"); }
__device__ __forceinline__ void mbar_expect(uint32_t b, uint32_t tx) { asm volatile("mbarrier.arrive.expect_tx.shared::cta.b64 _, [%0], %1;" ::"r"(b), "r"(tx) : "memory"); }
__device__ __forceinline__ void mbar_arrive(uint32_t b) { asm volatile("mbarrier.arrive.shared::cta.b64 _, [%0];" ::"r"(b) : "memory"); }
#define MBAR_WAIT_BODY(QUAL) "{.reg .pred p;\nLOOP:\nmbarrier.try_wait.parity" QUAL ".shared::cta.b64 p, [%0], %1;\n@!p bra LOOP;\n}"
__device__ __forceinline__ void mbar_wait(uint32_t b, uint32_t ph) { asm volatile(MBAR_WAIT_BODY("") ::"r"(b), "r"(ph) : "memory"); }
__device__ __forceinline__ void mbar_wait_cl(uint32_t b, uint32_t ph) { asm volatile(MBAR_WAIT_BODY(".acquire.cluster") ::"r"(b), "r"(ph) : "memory"); }
__device__ __forceinline__ void mbar_arrive_if(uint32_t b, uint32_t cond) {
    asm volatile("{.reg .pred p; setp.ne.u32 p, %1, 0; @p mbarrier.arrive.shared::cta.b64 _, [%0];}" ::"r"(b), "r"(cond) : "memory");
}
__device__ __forceinline__ bool elect_one() {
    uint32_t el;
    asm volatile("{.reg .pred p; elect.sync _|p, 0xffffffff; selp.u32 %0, 1, 0, p;}" : "=r"(el));
    return el != 0;
}
__device__ __forceinline__ uint32_t mapa(uint32_t a, uint32_t cta) { uint32_t r; asm("mapa.shared::cluster.u32 %0, %1, %2;" : "=r"(r) : "r"(a), "r"(cta)); return r; }
__device__ __forceinline__ void bar_sync(int id, int n) { asm volatile("bar.sync %0, %1;" ::"r"(id), "r"(n) : "memory"); }
__device__ __forceinline__ void bar_arrive(int id, int n) { asm volatile("bar.arrive %0, %1;" ::"r"(id), "r"(n) : "memory"); }
__device__ __forceinline__ void fence_async_smem() { asm volatile("fence.proxy.async.shared::cta;" ::: "memory"); }
__device__ __forceinline__ void fence_async_global() { asm volatile("fence.proxy.async.global;" ::: "memory"); }
__device__ __forceinline__ void tma2d(uint32_t dst, const CUtensorMap* m, int c0, int c1, uint32_t bar) {
    asm volatile("cp.async.bulk.tensor.2d.shared::cluster.global.mbarrier::complete_tx::bytes [%0], [%1, {%3, %4}], [%2];"
                 ::"r"(dst), "l"(m), "r"(bar), "r"(c0), "r"(c1) : "memory");
}
__device__ __forceinline__ void tma3d(uint32_t dst, const CUtensorMap* m, int c0, int c1, int c2, uint32_t bar) {
    asm volatile("cp.async.bulk.tensor.3d.shared::cluster.global.mbarrier::complete_tx::bytes [%0], [%1, {%3, %4, %5}], [%2];"
                 ::"r"(dst), "l"(m), "r"(bar), "r"(c0), "r"(c1), "r"(c2) : "memory");
}
__device__ __forceinline__ void poll_counter(const unsigned* p, unsigned target) {
    int it = 0;
    while (true) {
        unsigned v;
        asm volatile("ld.acquire.gpu.global.u32 %0, [%1];" : "=r"(v) : "l"(p) : "memory");
        if ((int)(v - target) >= 0) break;
        if (++it > (SPIN_LIMIT >> 2)) __trap();
    }
}
__device__ __forceinline__ void red_release(unsigned* p) { asm volatile("red.release.gpu.global.add.u32 [%0], 1;" ::"l"(p) : "memory"); }
__device__ __forceinline__ uint32_t pack2(float lo, float hi) { uint32_t r; asm("cvt.rn.bf16x2.f32 %0, %1, %2;" : "=r"(r) : "f"(hi), "f"(lo)); return r; }
__device__ __forceinline__ float bf_lo(uint32_t v) { return __uint_as_float(v << 16); }
__device__ __forceinline__ float bf_hi(uint32_t v) { return __uint_as_float(v & 0xffff0000u); }
__device__ __forceinline__ float ex2f(float x) { float r; asm("ex2.approx.ftz.f32 %0, %1;" : "=f"(r) : "f"(x)); return r; }
__device__ __forceinline__ float rcpf(float x) { float r; asm("rcp.approx.ftz.f32 %0, %1;" : "=f"(r) : "f"(x)); return r; }
__device__ __forceinline__ void sts128(uint32_t a, uint32_t x, uint32_t y, uint32_t z, uint32_t w) { asm volatile("st.shared.v4.b32 [%0], {%1,%2,%3,%4};" ::"r"(a), "r"(x), "r"(y), "r"(z), "r"(w) : "memory"); }
__device__ __forceinline__ void lds128(uint32_t a, uint32_t* r) { asm volatile("ld.shared.v4.b32 {%0,%1,%2,%3}, [%4];" : "=r"(r[0]), "=r"(r[1]), "=r"(r[2]), "=r"(r[3]) : "r"(a) : "memory"); }
__device__ __forceinline__ void lds64f(uint32_t a, float& x, float& y) { asm volatile("ld.shared.v2.f32 {%0,%1}, [%2];" : "+f"(x), "+f"(y) : "r"(a) : "memory"); }
__device__ __forceinline__ void ldsm4(uint32_t a, uint32_t* r) { asm volatile("ldmatrix.sync.aligned.m8n8.x4.shared.b16 {%0,%1,%2,%3}, [%4];" : "=r"(r[0]), "=r"(r[1]), "=r"(r[2]), "=r"(r[3]) : "r"(a) : "memory"); }
__device__ __forceinline__ void stsm4(uint32_t a, uint32_t x, uint32_t y, uint32_t z, uint32_t w) { asm volatile("stmatrix.sync.aligned.m8n8.x4.shared.b16 [%0], {%1,%2,%3,%4};" ::"r"(a), "r"(x), "r"(y), "r"(z), "r"(w) : "memory"); }
__device__ __forceinline__ void ld_poll128(const uint4* p, uint32_t* r) { asm volatile("ld.relaxed.gpu.global.v4.b32 {%0,%1,%2,%3}, [%4];" : "=r"(r[0]), "=r"(r[1]), "=r"(r[2]), "=r"(r[3]) : "l"(p) : "memory"); }

__device__ __forceinline__ void mma16816_acc(float* c, const uint32_t* a, uint32_t b0, uint32_t b1) {
    asm volatile("mma.sync.aligned.m16n8k16.row.col.f32.bf16.bf16.f32 {%0,%1,%2,%3}, {%4,%5,%6,%7}, {%8,%9}, {%0,%1,%2,%3};"
                 : "+f"(c[0]), "+f"(c[1]), "+f"(c[2]), "+f"(c[3]) : "r"(a[0]), "r"(a[1]), "r"(a[2]), "r"(a[3]), "r"(b0), "r"(b1));
}
__device__ __forceinline__ void wg_fence() { asm volatile("wgmma.fence.sync.aligned;" ::: "memory"); }
__device__ __forceinline__ void wg_commit() { asm volatile("wgmma.commit_group.sync.aligned;" ::: "memory"); }
template <int N> __device__ __forceinline__ void wg_wait() { asm volatile("wgmma.wait_group.sync.aligned %0;" ::"n"(N) : "memory"); }
template <int N> __device__ __forceinline__ void reg_fence(float* d) {
#pragma unroll
    for (int i = 0; i < N; i++) asm volatile("" : "+f"(d[i])::"memory");
}

#define A4(c, d, o) c(d[o + 0]), c(d[o + 1]), c(d[o + 2]), c(d[o + 3])
#define A8(c, d, o) A4(c, d, o), A4(c, d, o + 4)
#define WGMMA_(SC, C0, TXT, OUTS, ...) do { \
        if constexpr (SC) asm volatile("{.reg .pred p; setp.eq.b32 p, 0, 0;\n" TXT "}\n" : OUTS("+f") : __VA_ARGS__); \
        else asm volatile("{.reg .pred p; setp.ne.b32 p, 0, 0;\n" TXT "}\n" : OUTS(C0) : __VA_ARGS__); \
    } while (0)
#define WGMMA(SC, ...) WGMMA_(SC, "=f", __VA_ARGS__)
template <int SC>
__device__ __forceinline__ void wgmma_rs64(float* d, const uint32_t* a, uint64_t db) {
#define O_(c) A8(c, d, 0), A8(c, d, 8), A8(c, d, 16), A8(c, d, 24)
#define T_ "wgmma.mma_async.sync.aligned.m64n64k16.f32.bf16.bf16 " \
           "{%0,%1,%2,%3,%4,%5,%6,%7,%8,%9,%10,%11,%12,%13,%14,%15,%16,%17,%18,%19,%20,%21,%22,%23,%24,%25,%26,%27,%28,%29,%30,%31}, " \
           "{%32,%33,%34,%35}, %36, p, 1, 1, 1;"
    if constexpr (SC == 2) WGMMA(0, T_, O_, "r"(a[0]), "r"(a[1]), "r"(a[2]), "r"(a[3]), "l"(db));
    else WGMMA_(SC, "+f", T_, O_, "r"(a[0]), "r"(a[1]), "r"(a[2]), "r"(a[3]), "l"(db));
#undef T_
#undef O_
}
template <int SC>
__device__ __forceinline__ void wgmma_rs48(float* d, const uint32_t* a, uint64_t db) {
#define O_(c) A8(c, d, 0), A8(c, d, 8), A8(c, d, 16)
    WGMMA_(SC, "+f", "wgmma.mma_async.sync.aligned.m64n48k16.f32.bf16.bf16 "
              "{%0,%1,%2,%3,%4,%5,%6,%7,%8,%9,%10,%11,%12,%13,%14,%15,%16,%17,%18,%19,%20,%21,%22,%23}, "
              "{%24,%25,%26,%27}, %28, p, 1, 1, 1;", O_, "r"(a[0]), "r"(a[1]), "r"(a[2]), "r"(a[3]), "l"(db));
#undef O_
}
template <int SC>
__device__ __forceinline__ void wgmma_ss40(float* d, uint64_t da, uint64_t db) {
#define O_(c) A8(c, d, 0), A8(c, d, 8), A4(c, d, 16)
    WGMMA(SC, "wgmma.mma_async.sync.aligned.m64n40k16.f32.bf16.bf16 "
              "{%0,%1,%2,%3,%4,%5,%6,%7,%8,%9,%10,%11,%12,%13,%14,%15,%16,%17,%18,%19}, %20, %21, p, 1, 1, 1, 1;", O_, "l"(da), "l"(db));
#undef O_
}
template <int SC>
__device__ __forceinline__ void wgmma_ss24(float* d, uint64_t da, uint64_t db) {
#define O_(c) A8(c, d, 0), A4(c, d, 8)
    WGMMA(SC, "wgmma.mma_async.sync.aligned.m64n24k16.f32.bf16.bf16 {%0,%1,%2,%3,%4,%5,%6,%7,%8,%9,%10,%11}, %12, %13, p, 1, 1, 0, 1;",
          O_, "l"(da), "l"(db));
#undef O_
}
__device__ __forceinline__ void wgmma_ss16(float* d, uint64_t da, uint64_t db) {
#define O_(c) A8(c, d, 0)
    WGMMA(0, "wgmma.mma_async.sync.aligned.m64n16k16.f32.bf16.bf16 {%0,%1,%2,%3,%4,%5,%6,%7}, %8, %9, p, 1, 1, 0, 1;", O_, "l"(da), "l"(db));
#undef O_
}
template <int N, int NK, bool FIRST>
__device__ __forceinline__ void mma_group(float* acc, const uint32_t* a, uint64_t desc) {
#pragma unroll
    for (int k = 0; k < NK; k++) {
        if (N == 64) { if (FIRST && k == 0) wgmma_rs64<0>(acc, a + 4 * k, desc + k * 128); else wgmma_rs64<1>(acc, a + 4 * k, desc + k * 128); }
        else         { if (FIRST && k == 0) wgmma_rs48<0>(acc, a + 4 * k, desc + k * 128); else wgmma_rs48<1>(acc, a + 4 * k, desc + k * 128); }
    }
}
__device__ __forceinline__ void red128(float* p, float a, float b, float c, float d) {
    asm volatile("red.relaxed.gpu.global.add.v4.f32 [%0], {%1,%2,%3,%4};" ::"l"(p), "f"(a), "f"(b), "f"(c), "f"(d) : "memory");
}
__device__ __forceinline__ uint32_t bar_addr(uint32_t sb, uint32_t i) { return sb + OFF_BAR + i * 8; }

__device__ __forceinline__ int fcol(int c, uint32_t rank) { return rank ? (c == 2 ? 0 : 48 + c * 64) : c * 64; }
__device__ __forceinline__ uint32_t hmul2(uint32_t a, uint32_t b) { uint32_t r; asm("mul.rn.bf16x2 %0, %1, %2;" : "=r"(r) : "r"(a), "r"(b)); return r; }
__device__ __forceinline__ void sched_fence() { asm volatile("pmevent 0;" ::: "memory"); }
template <int NP, int NB>
__device__ __forceinline__ void gelu_pipe(uint32_t* out, float* acc, uint32_t bb, uint32_t zero) {
    constexpr int G = 4, LAG = 1, N = 2 * NP / G;
    float w[32];
#pragma unroll
    for (int b = 0; b < N + 1 + LAG; b++) {
        if (b >= 1 && b <= N) {
#pragma unroll
            for (int i = (b - 1) * G; i < b * G; i++) asm volatile("tanh.approx.f32 %0, %0;" : "+f"(w[i]));
        }
        if (b < N) {
#pragma unroll
            for (int i = b * G; i < (b + 1) * G; i++)
                asm volatile("{.reg .f32 t; mul.rn.f32 t, %1, %1; fma.rn.f32 t, t, 0f3E922279, 0f3FCC422A; mul.rn.f32 %0, t, %1;}" : "=f"(w[i]) : "f"(acc[i]));
        }
        if (b >= 1 + LAG) {
#pragma unroll
            for (int i = (b - 1 - LAG) * G; i < (b - LAG) * G; i += 2) {
                asm volatile("{.reg .f32 x, y; fma.rn.f32 x, %1, %2, %1; fma.rn.f32 y, %3, %4, %3; cvt.rn.bf16x2.f32 %0, y, x;}"
                             : "=r"(out[i >> 1]) : "f"(acc[i]), "f"(w[i]), "f"(acc[i + 1]), "f"(w[i + 1]));
                if ((i >> 1) < NB) lds64f(bb + (i >> 2) * 32 + ((i & 2) ? zero : 0u), acc[i], acc[i + 1]);
            }
        }
        if (b < N + LAG) sched_fence();
    }
}
template <bool NEG, int I0, int I1, int ST = 4>
__device__ __forceinline__ void sm_exp(const float* t, uint32_t* e, float& s) {
#pragma unroll
    for (int i = I0; i < I1; i++) {
        const float x0 = ex2f(NEG ? -t[ST * i] : t[ST * i]), x1 = ex2f(NEG ? -t[ST * i + 1] : t[ST * i + 1]);
        s = (i == 0) ? x0 + x1 : (s + x0) + x1;
        e[i] = pack2(x0, x1);
    }
}
__device__ __forceinline__ void sm_store(const uint32_t* e, float r, uint32_t a0, uint32_t a1) {
    const uint32_t r2 = pack2(r, r);
    sts128(a0, hmul2(e[0], r2), hmul2(e[1], r2), hmul2(e[2], r2), hmul2(e[3], r2));
    sts128(a1, hmul2(e[4], r2), hmul2(e[5], r2), hmul2(e[6], r2), hmul2(e[7], r2));
}
__device__ __forceinline__ void sm_store_raw(const uint32_t* e, uint32_t a0, uint32_t a1) {
    sts128(a0, e[0], e[1], e[2], e[3]);
    sts128(a1, e[4], e[5], e[6], e[7]);
}
__device__ __forceinline__ void st_async128(uint32_t a, uint32_t x, uint32_t y, uint32_t z, uint32_t w, uint32_t bar) {
    asm volatile("st.async.weak.shared::cluster.mbarrier::complete_tx::bytes.v4.b32 [%0], {%1,%2,%3,%4}, [%5];" ::"r"(a), "r"(x), "r"(y), "r"(z), "r"(w), "r"(bar) : "memory");
}
__device__ __forceinline__ uint32_t phik_addr(uint32_t R, int wq, int ln) {
    const int t = ln & 3, g = (ln >> 2) ^ (t & 2);
    return R + R_PHI + (t >> 1) * 8192 + (wq * 16 + g) * 128 + ((((t & 1) * 4) ^ g) << 4);
}
__device__ __forceinline__ uint32_t phiq_addr(uint32_t R, int wq, int ln) {
    const int g = ln >> 2, t = ln & 3;
    return R + R_PHI + (wq * 16 + g) * 128 + (((2 * t) ^ g) << 4);
}
__device__ __forceinline__ void row_redo(const float* p, uint32_t* ep, float& sp, uint32_t* en, float& sn) {
    {
        float mx = p[0], mn = p[0];
#pragma unroll
        for (int i = 1; i < 16; i++) { mx = fmaxf(mx, p[(i >> 1) * 4 + (i & 1)]); mn = fminf(mn, p[(i >> 1) * 4 + (i & 1)]); }
        float u[16];
#pragma unroll
        for (int i = 0; i < 16; i++) u[i] = p[(i >> 1) * 4 + (i & 1)] - mx;
        sm_exp<false, 0, 8, 2>(u, ep, sp);
#pragma unroll
        for (int i = 0; i < 16; i++) u[i] = p[(i >> 1) * 4 + (i & 1)] - mn;
        sm_exp<true, 0, 8, 2>(u, en, sn);
    }
}
__device__ __forceinline__ void poll_partial(const uint4* p, uint32_t* v, uint32_t tag) {
#define TAG_TEST \
    "lop3.b32 a, %0, %4, %17, 0x7E;\n"        \
    "lop3.b32 b, %8, %12, %17, 0x7E;\n" \
    "lop3.b32 a, a, b, 1, 0xA8;\n"            \
    "setp.eq.u32 p, a, 0;\n" \
    "vote.sync.all.pred p, p, 0xffffffff;\n" \
    "@p bra.uni DONE;\n"
    asm volatile("{.reg .pred p; .reg .b32 a, b, it;\n"
                 TAG_TEST
                 "mov.u32 it, 0;\n"
                 "LOOP:\n"
                 "ld.relaxed.gpu.global.v4.b32 {%0,%1,%2,%3}, [%16];\n"
                 "ld.relaxed.gpu.global.v4.b32 {%4,%5,%6,%7}, [%16+512];\n"
                 "ld.relaxed.gpu.global.v4.b32 {%8,%9,%10,%11}, [%16+1024];\n"
                 "ld.relaxed.gpu.global.v4.b32 {%12,%13,%14,%15}, [%16+1536];\n"
                 TAG_TEST
                 "add.u32 it, it, 1;\n"
                 "setp.lt.u32 p, it, 1048576;\n"
                 "@p bra.uni LOOP;\n"
                 "trap;\n"
                 "DONE:\n}"
                 : "+r"(v[0]), "+r"(v[1]), "+r"(v[2]), "+r"(v[3]), "+r"(v[4]), "+r"(v[5]), "+r"(v[6]), "+r"(v[7]),
                   "+r"(v[8]), "+r"(v[9]), "+r"(v[10]), "+r"(v[11]), "+r"(v[12]), "+r"(v[13]), "+r"(v[14]), "+r"(v[15])
                 : "l"(p), "r"(tag) : "memory");
}
__device__ __forceinline__ void send_partial(uint4* dst, const float* acc, uint32_t tag) {
#pragma unroll
    for (int v = 0; v < 4; v++)
        asm volatile("st.relaxed.gpu.global.v4.b32 [%0], {%1,%2,%3,%4};" ::"l"(dst + v * 32), "r"((pack2(acc[8 * v], acc[8 * v + 1]) & ~1u) | tag),
                     "r"(pack2(acc[8 * v + 2], acc[8 * v + 3])), "r"(pack2(acc[8 * v + 4], acc[8 * v + 5])), "r"(pack2(acc[8 * v + 6], acc[8 * v + 7])) : "memory");
}

}

__global__ void __launch_bounds__(NTHREADS, 1)
fused_hedgehog_gelu_kernel(const __grid_constant__ CUtensorMap tm_x, const __grid_constant__ CUtensorMap tm_x2, const __grid_constant__ CUtensorMap tm_wqkv,
                           const __grid_constant__ CUtensorMap tm_w1, const __grid_constant__ CUtensorMap tm_w2,
                           const __grid_constant__ CUtensorMap tm_wo,
                           const __nv_bfloat16* __restrict__ wqkv,
                           const __nv_bfloat16* __restrict__ wphi, const __nv_bfloat16* __restrict__ wo,
                           const __nv_bfloat16* __restrict__ w1, const __nv_bfloat16* __restrict__ b1,
                           const __nv_bfloat16* __restrict__ w2, const __nv_bfloat16* __restrict__ b2,
                           __nv_bfloat16* __restrict__ out, const __grid_constant__ SlotDesc sd) {
    asm volatile("prefetch.tensormap [%0];" ::"l"(&tm_x) : "memory");
    extern __shared__ __align__(1024) uint8_t smem_raw[];
    const uint32_t sb = __shfl_sync(0xffffffffu, smem_u32(smem_raw), 0);
    const uint32_t cta = __shfl_sync(0xffffffffu, blockIdx.x, 0);
    const int cl = cta >> 1;
    const uint32_t rank = cta & 1;
    const int rb = (cl & 3) + 4 * (cl >> 4), pr = (cl >> 2) & 3;
    const int cs = pr * 2 + rank, bid = rb * 8 + cs;

    const int warp = __shfl_sync(0xffffffffu, threadIdx.x >> 5, 0);
    const int lane = __shfl_sync(0xffffffffu, threadIdx.x & 31, threadIdx.x & 31);
    if (warp == 0 && elect_one()) {
#pragma unroll
        for (int i = 0; i < 12; i++) {
            const uint32_t b = bar_addr(sb, i < 8 ? B_X + i : ((i & 1) ? B_FULL : B_V) + ((i - 8) >> 1));
            mbar_init(b, 1);
            asm volatile("fence.mbarrier_init.release.cluster;" ::: "memory");
            mbar_expect(b, 16384);
            if (i < 8) tma3d(sb + OFF_X + (i ^ 4) * 16384, &tm_x, 0, rb * 128 + (i >> 2) * 64, (i & 3) * 2, b);
            else tma2d(sb + OFF_RING + (i - 8) * 16384, &tm_wqkv, 512 + cs * 64, (i - 8) * 128, b);
        }
    }
    __syncwarp();
    if (warp >= 8) {
        asm volatile("setmaxnreg.dec.sync.aligned.u32 24;");
        if (warp == 8) {
            asm volatile("barrier.cluster.arrive.relaxed.aligned;" ::: "memory");
            asm volatile("barrier.cluster.wait.aligned;" ::: "memory");
            if (elect_one()) {
                if ((sb & 0x3FFFF) != SMEM_BASE) __trap();
                unsigned epoch;
                asm volatile("ld.relaxed.gpu.global.u32 %0, [%1];" : "=r"(epoch) : "l"(g_epoch + bid * 8) : "memory");
#pragma unroll
                for (int hf = 2; hf < 20; hf++) {
                    const int ch = hf >> 1, h = hf & 3, up = hf & 1;
                    if (hf == 10) {
                        TSL(0);
                        poll_counter(g_cnt_fold + cs * 32, (epoch + 1) * 16);
                        fence_async_global();
                        asm volatile("st.relaxed.gpu.global.u32 [%0], %1;" ::"l"(g_epoch + bid * 8), "r"(epoch + 1) : "memory");
                        TSL(1);
                    }
                    if (hf == 16) {
                        const uint32_t xr = bar_addr(sb, B_XR);
                        const int xc = rank * 256 + ((pr + 3) & 3) * 64;
                        mbar_wait(bar_addr(sb, B_HD0), 0);
                        mbar_expect(xr, 16384 + 128);
                        tma2d(sb + OFF_XR, &tm_x2, xc, rb * 128, xr);
                        asm volatile("cp.async.bulk.shared::cluster.global.mbarrier::complete_tx::bytes [%0], [%1], 128, [%2];"
                                     ::"r"(sb + OFF_XR + 16384), "l"(b2 + xc), "r"(xr) : "memory");
                    }
                    const int sl = (hf >= 17) ? hf - 1 : hf;
                    if (hf >= 3 && hf != 17) mbar_wait(bar_addr(sb, hf == 3 ? B_XD : B_EMPTY + (sl & 3)), ((sl >> 2) & 1) ^ (hf != 3));
                    const uint32_t fb = bar_addr(sb, B_FULL + h), dst = sb + ((hf == 17) ? OFF_REG + R_PHI : OFF_RING + (sl & 3) * 32768);
                    mbar_expect(fb, 32768);
                    if (ch == 5) {
                        asm volatile("cp.async.bulk.shared::cluster.global.mbarrier::complete_tx::bytes [%0], [%1], 32768, [%2];"
                                     ::"r"(dst), "l"(g_wfold + cs * 4096 + up * 2048), "r"(fb) : "memory");
                    } else {
                        const CUtensorMap* m = (ch == 1) ? &tm_wqkv : (ch < 5) ? &tm_w1 : &tm_w2;
                        const int c0 = (ch == 1) ? 1024 + cs * 64 : (ch < 5) ? cs * 176 + fcol(ch - 2, rank) : rank * 256 + ((pr + ch - 5) & 3) * 64;
                        const bool p2 = ch > 5;
                        const int c1 = p2 ? pr * 352 + (up ? 128 : rank * 224) : up * 256;
                        const int c2 = p2 ? (up ? pr * 128 : pr * 352 + 224 - rank * 224) : c1 + 128;
                        tma2d(dst, m, c0, c1, fb);
                        tma2d(dst + (hf == 17 ? RSTEP : 16384), (p2 && up) ? &tm_wo : m, c0, c2, fb);
                    }
                    TSL(16 + hf);
                }
            }
        } else {
            const int ht = threadIdx.x - 288;
            if (ht == 32) {
                mbar_init(bar_addr(sb, B_FULL + 2), 1); mbar_init(bar_addr(sb, B_FULL + 3), 1);
#pragma unroll
                for (int i = 0; i < 4; i++) mbar_init(bar_addr(sb, B_EMPTY + i), 8);
                mbar_init(bar_addr(sb, B_XD), 4); mbar_init(bar_addr(sb, B_XD0), 4); mbar_init(bar_addr(sb, B_BPHI), 64);
                mbar_init(bar_addr(sb, B_FI), 64); mbar_init(bar_addr(sb, B_FO), 128); mbar_init(bar_addr(sb, B_RXG), 1); mbar_init(bar_addr(sb, B_HD0), 4);
                asm volatile("fence.mbarrier_init.release.cluster;" ::: "memory");
            }
            if (ht == 0) {
#pragma unroll
                for (int i = 0; i < 8; i++) mbar_init(bar_addr(sb, B_HXF + i), 1);
                mbar_init(bar_addr(sb, B_KVP), 129); mbar_init(bar_addr(sb, B_KVB), 96); mbar_init(bar_addr(sb, B_AUX), 65);
                mbar_init(bar_addr(sb, B_XR), 1);
#pragma unroll
                for (int i = 0; i < 6; i++) mbar_expect(bar_addr(sb, B_HXF + i), i < 2 ? 14336 : 8192);
                asm volatile("fence.mbarrier_init.release.cluster;" ::: "memory");
                asm volatile("fence.release.sync_restrict::shared::cta.cluster;" ::: "memory");
            }
            __syncwarp();
            asm volatile("barrier.cluster.arrive.relaxed.aligned;" ::: "memory");
            if (warp == 9) {
                unsigned epoch;
                asm volatile("ld.relaxed.gpu.global.u32 %0, [%1];" : "=r"(epoch) : "l"(g_epoch + bid * 8) : "memory");
                float4* zp = (float4*)(g_kv + cs * KVN + rb * (KVN / 16));
                zp[lane] = make_float4(0.f, 0.f, 0.f, 0.f);
                if (lane < KVN / 64 - 32) zp[32 + lane] = make_float4(0.f, 0.f, 0.f, 0.f);
                sts128(sb + OFF_ONES + 1024 + lane * 32, epoch & 1u, 0u, 0u, 0u);
                sts128(sb + OFF_ONES + 1040 + lane * 32, epoch & 1u, 0u, 0u, 0u);
                fence_async_smem();
                asm volatile("barrier.cluster.wait.aligned;" ::: "memory");
                if (elect_one()) {
                    red_release(g_cnt_zero + cs * 32);
                    mbar_wait(bar_addr(sb, B_FULL + 2), 0);
                    TSL(11);
                    asm volatile("prefetch.tensormap [%0];" ::"l"(&tm_w1) : "memory");
                    asm volatile("cp.async.bulk.prefetch.L2.global [%0], %1;" ::"l"((const char*)w1 + (size_t)bid * 11008), "r"(11008) : "memory");
                    poll_counter(g_cnt_zero + cs * 32, (epoch + 1) * 16);
                    mbar_wait(bar_addr(sb, B_FULL + 3), 0);
                    mbar_arrive(bar_addr(sb, B_AUX));
                    TSL(12);
                    asm volatile("prefetch.tensormap [%0];" ::"l"(&tm_w2) : "memory");
                    asm volatile("prefetch.tensormap [%0];" ::"l"(&tm_wo) : "memory");
                    asm volatile("prefetch.tensormap [%0];" ::"l"(&tm_x2) : "memory");
                    asm volatile("cp.async.bulk.prefetch.L2.global [%0], %1;" ::"l"((const char*)w2 + (size_t)bid * 11008), "r"(11008) : "memory");
                    asm volatile("cp.async.bulk.prefetch.L2.global [%0], %1;" ::"l"((const char*)wo + (size_t)bid * 4096), "r"(4096) : "memory");
                    asm volatile("prefetch.global.L2 [%0];" ::"l"(b2 + cs * 64) : "memory");
#pragma unroll 1
                    for (int i = 0; i < 12; i++) {
                        const int j = i >> 2;
                        const uint4* dst = g_part + (size_t)((bid & ~7) | (int)rank) * 3072 + ((pr + 1 + j) & 3) * 6144 + j * 1024 + (i & 3) * 256;
#pragma unroll
                        for (int k = 0; k < 4; k++)
                            asm volatile("cp.async.bulk.global.shared::cta.bulk_group [%0], [%1], 1024;" ::"l"(dst + k * 64), "r"(sb + OFF_ONES + 1024) : "memory");
                        __nanosleep(40);
                    }
                    asm volatile("cp.async.bulk.commit_group;" ::: "memory");
                    asm volatile("cp.async.bulk.wait_group 0;" ::: "memory");
                    fence_async_global();
                    TSL(9);
                    asm volatile("st.shared.b32 [%0], %1;" ::"r"(bar_addr(sb, B_TAG)), "r"((epoch + 1) & 1u) : "memory");
                    mbar_arrive(bar_addr(sb, B_KVP));
                }
                __syncwarp();
            } else {
                const int u = ht - 32;
                const uint4 w0 = *(const uint4*)(wphi + cs * 1024 + u * 16), w1_ = *(const uint4*)(wphi + cs * 1024 + u * 16 + 8);
                sts128(sb + OFF_ONES + u * 16, 0x3f803f80u, 0x3f803f80u, 0x3f803f80u, 0x3f803f80u);
                if (u < 44) {
                    const int gc = cs * 176 + u * 4;
                    uint2 bw = make_uint2(0u, 0u);
                    if (gc < FF) bw = *(const uint2*)(b1 + gc);
                    sts128(sb + OFF_B1 + u * 16, __float_as_uint(0.5f * bf_lo(bw.x)), __float_as_uint(0.5f * bf_hi(bw.x)),
                           __float_as_uint(0.5f * bf_lo(bw.y)), __float_as_uint(0.5f * bf_hi(bw.y)));
                }
                asm volatile("barrier.cluster.wait.aligned;" ::: "memory");
                mbar_wait(bar_addr(sb, B_XD0), 0);
                {
                    const uint32_t ra = sb + OFF_BPHI + u * 128, wa = (u >> 4) * 4, sw = (u & 7) << 4;
                    uint32_t wv[8] = {w0.x, w0.y, w0.z, w0.w, w1_.x, w1_.y, w1_.z, w1_.w};
#pragma unroll
                    for (int i = 0; i < 8; i++) wv[i] = pack2(bf_lo(wv[i]) * 2.8853900817779268f, bf_hi(wv[i]) * 2.8853900817779268f);
#pragma unroll
                    for (int i = 0; i < 8; i++) {
                        sts128(ra + ((i << 4) ^ sw), 0u, 0u, 0u, 0u);
                        asm volatile("st.shared.b32 [%0], %1;" ::"r"(ra + ((i << 4) ^ sw) + wa), "r"(wv[i]) : "memory");
                    }
                    const uint32_t pw = sb + OFF_FIN + 4096 + u * 32 + ((u & 4) << 2);
                    sts128(pw, wv[0], wv[1], wv[2], wv[3]);
                    sts128(pw ^ 16, wv[4], wv[5], wv[6], wv[7]);
                }
                fence_async_smem();
                mbar_arrive(bar_addr(sb, B_BPHI));
                mbar_wait(bar_addr(sb, B_FULL + 2), 0);
                mbar_arrive(bar_addr(sb, B_AUX));
                {
                    const int r = u >> 3, ch = u & 7;
                    const __nv_bfloat16* wr = wqkv + (size_t)(rb * 32 + r) * 1536 + cs * 64 + ch * 8;
#pragma unroll 1
                    for (int i = 0; i < 4; i += 2) {
                        const uint4 a = __ldcg((const uint4*)(wr + i * 8 * 1536)), b = __ldcg((const uint4*)(wr + (i + 1) * 8 * 1536));
                        const uint32_t d = sb + OFF_FIN + r * 128 + ((ch ^ r) << 4) + i * 1024;
                        sts128(d, a.x, a.y, a.z, a.w);
                        sts128(d + 1024, b.x, b.y, b.z, b.w);
                    }
                }
                fence_async_smem();
                mbar_arrive(bar_addr(sb, B_FI));
                if (warp == 10 && elect_one()) {
                    mbar_wait(bar_addr(sb, B_FO), 0);
                    asm volatile("cp.async.bulk.global.shared::cta.bulk_group [%0], [%1], 4096;" ::"l"(g_wfold + cs * 4096 + rb * 256), "r"(sb + OFF_FOUT) : "memory");
                    asm volatile("cp.async.bulk.commit_group;" ::: "memory");
                    asm volatile("cp.async.bulk.wait_group 0;" ::: "memory");
                    fence_async_global();
                    asm volatile("red.relaxed.gpu.global.add.u32 [%0], 1;" ::"l"(g_cnt_fold + cs * 32) : "memory");
                    asm volatile("fence.release.sync_restrict::shared::cta.cluster;" ::: "memory");
                    asm volatile("mbarrier.arrive.relaxed.cluster.shared::cluster.b64 _, [%0];" ::"r"(mapa(bar_addr(sb, B_RXG), rank ^ 1)) : "memory");
                    TSL(2);
                }
                __syncwarp();
            }
            mbar_wait(bar_addr(sb, B_KVP), 0);
            if (ht == 32) TSL(3);
            __nanosleep(400);
            const uint4* src = (const uint4*)(g_kv + cs * KVN) + (11 - warp) * 96 + lane;
            uint32_t ka = sb + OFF_KVB + (11 - warp) * 256 + lane * 4;
            const uint32_t zo = 2 * RSTEP + (lane & 1) * 124;
#pragma unroll 1
            for (int uu = 11 - warp; uu < 8; uu += 3, src += 288, ka += 768) {
                uint32_t v[12];
                int it = 0;
                do {
#pragma unroll
                    for (int i = 0; i < 3; i++) ld_poll128(src + i * 32, v + 4 * i);
                    if (++it > (SPIN_LIMIT >> 2)) __trap();
                } while (__any_sync(0xffffffffu, v[3] != 0x41800000u || v[7] != 0x41800000u || v[11] != 0x41800000u));
                const float* a = (const float*)v;
                asm volatile("st.shared.b32 [%0], %1;" ::"r"(ka), "r"(pack2(a[0], a[1])) : "memory");
                asm volatile("st.shared.b32 [%0], %1;" ::"r"(ka + RSTEP), "r"(pack2(a[2], a[8])) : "memory");
                asm volatile("st.shared.b32 [%0], %1;" ::"r"(ka + 128), "r"(pack2(a[4], a[5])) : "memory");
                asm volatile("st.shared.b32 [%0], %1;" ::"r"(ka + RSTEP + 128), "r"(pack2(a[6], a[9])) : "memory");
                const float zh = fmaf(a[10], 0.5f, (uu & 1) ? 0.f : 0.5e-6f);
                asm volatile("st.shared.v2.b32 [%0], {%1, %1};" ::"r"(ka + zo), "r"(pack2(zh, zh)) : "memory");
                if (ht == 64 && uu == 0) TSL(5);
            }
            fence_async_smem();
            mbar_arrive(bar_addr(sb, B_KVB));
            if (ht == 64) TSL(6);
        }
    } else {
        asm volatile("setmaxnreg.inc.sync.aligned.u32 240;");
        const int wg = warp >> 2, wq = warp & 3, tid = wq * 32 + lane;
        const int row0 = rb * 128 + wg * 64 + wq * 16;
        const uint32_t xs = sb + OFF_X + (wg ^ 1) * 65536, xb = bar_addr(sb, B_X + wg * 4);

        asm volatile("barrier.cluster.arrive.relaxed.aligned;" ::: "memory");
        const uint32_t R = sb + OFF_REG + (wg ^ 1) * RSTEP;
        const uint32_t zero = (uint32_t)warp >> 8;
        const uint32_t lead = (wg == 0), rel1 = (wg == 1 && lane == 0);

        uint32_t xa[128];
        {
            asm volatile("barrier.cluster.wait.aligned;" ::: "memory");
            float st[2][5][4];
#pragma unroll
            for (int i = 0; i < 40; i++) (&st[0][0][0])[i] = 0.f;
            const int lr = lane & 15, lc = lane >> 4;
            uint32_t la[4];
#pragma unroll
            for (int k = 0; k < 4; k++) la[k] = xs + (wq * 16 + lr) * 128 + (((2 * k + lc) ^ (lr & 7)) << 4);
#pragma unroll
            for (int q = 0; q < 4; q++) {
                mbar_wait(xb + q * 8, 0);
#pragma unroll
                for (int k = 8 * q; k < 8 * q + 8; k++) ldsm4(la[k & 3] + (k >> 2) * 8192, xa + 4 * k);
#pragma unroll
                for (int k = 8 * q; k < 8 * q + 8; k++) {
                    const uint32_t* a = xa + 4 * k;
                    float (*c)[4] = st[k & 1];
                    mma16816_acc(c[0], a, 0x3f803f80u, 0x3f803f80u);
                    mma16816_acc(c[1 + (k & 2)], a, a[0], a[2]); mma16816_acc(c[2 + (k & 2)], a, a[1], a[3]);
                }
            }
            sched_fence();
            if (wg == 1) bar_arrive(1, 256);
            sched_fence();
            const bool odd = (lane >> 2) & 1;
            const int src = (lane & 28) | (lane >> 3);
            const float s0 = st[0][0][0] + st[1][0][0], s1 = st[0][0][2] + st[1][0][2];
            const float q0 = __shfl_sync(0xffffffffu, odd ? (st[0][1][1] + st[0][3][1]) + (st[1][1][1] + st[1][3][1])
                                                           : (st[0][1][0] + st[0][3][0]) + (st[1][1][0] + st[1][3][0]), src);
            const float q1 = __shfl_sync(0xffffffffu, odd ? (st[0][2][3] + st[0][4][3]) + (st[1][2][3] + st[1][4][3])
                                                           : (st[0][2][2] + st[0][4][2]) + (st[1][2][2] + st[1][4][2]), src);
            mbar_arrive_if(bar_addr(sb, wg ? B_XD : B_XD0), lane == 0);
            float m0 = s0 * (1.f / DM), m1 = s1 * (1.f / DM);
            const float h0 = 0.5f * rsqrtf(fmaxf(fmaf(-m0, m0, q0 * (1.f / DM)), 0.f) + 1e-5f);
            const float h1 = 0.5f * rsqrtf(fmaxf(fmaf(-m1, m1, q1 * (1.f / DM)), 0.f) + 1e-5f);
            if (__builtin_expect(__any_sync(0xffffffffu, !(fmaxf(fabsf(m0 * h0), fabsf(m1 * h1)) < 0.125f)), 0)) {
                const uint32_t mm0 = pack2(m0, m0), mm1 = pack2(m1, m1);
#pragma unroll
                for (int i = 0; i < 128; i++) asm volatile("sub.rn.bf16x2 %0, %0, %1;" : "+r"(xa[i]) : "r"((i & 1) ? mm1 : mm0));
                m0 -= bf_lo(mm0); m1 -= bf_lo(mm1);
            }
            const uint32_t sc0 = pack2(h0, h0), sc1 = pack2(h1, h1);
            const uint32_t of0 = pack2(-m0 * bf_lo(sc0), -m0 * bf_lo(sc0)), of1 = pack2(-m1 * bf_lo(sc1), -m1 * bf_lo(sc1));
#pragma unroll
            for (int i = 0; i < 128; i++) asm volatile("fma.rn.bf16x2 %0, %0, %1, %2;" : "+r"(xa[i]) : "r"((i & 1) ? sc1 : sc0), "r"((i & 1) ? of1 : of0));
        }

        const uint32_t rel0 = (wg == 0 && lane == 0);
        const int turn = 1 + wg, other = 2 - wg;
        float acc[32], tt[32];
        uint32_t hf[44];

#define FULL(S, H) mbar_wait(bar_addr(sb, B_FULL + ((S) & 1) * 2 + (H)), ((S) >> 1) & 1)
#define REL_MID(S) do { wg_wait<1>(); mbar_arrive_if(bar_addr(sb, B_EMPTY + ((S) & 1) * 2), rel1); TSD(S); } while (0)
#define TSD(S) do { TSW(2 + 2 * (S)); if ((S) > 0) TSW2(1 + 2 * (S)); } while (0)
#define SLOT_END(S) do { wg_wait<0>(); reg_fence<32>(acc); mbar_arrive_if(bar_addr(sb, B_EMPTY + ((S) & 1) * 2 + 1), rel0 | rel1); mbar_arrive_if(bar_addr(sb, B_EMPTY + ((S) & 1) * 2), rel0); TSR2(); sched_fence(); } while (0)
#define SLOT1_REST(S, N, MID, MID2) do { \
            mma_group<N, 4, false>(acc, xa + 32, sd.d[S] + 1024); \
            FULL(S, 1); \
            mma_group<N, 4, false>(acc, xa + 48, sd.d[S] + 1536); wg_commit(); \
            MID; \
            mma_group<N, 6, false>(acc, xa + 64, sd.d[S] + 2048); wg_commit(); \
            REL_MID(S); \
            mma_group<N, 4, false>(acc, xa + 88, sd.d[S] + 2816); \
            MID2; \
            mma_group<N, 5, false>(acc, xa + 104, sd.d[S] + 3328); \
            bar_arrive(other, 256); TSB(); \
            mma_group<N, 1, false>(acc, xa + 124, sd.d[S] + 3968); wg_commit(); \
        } while (0)
#define TURN(S) do { FULL(S, 0); TSR(); sched_fence(); bar_sync(turn, 256); TSA(); wg_fence(); } while (0)
#define SLOT1_HEAD_ST(S, N, C) do { \
            TURN(S); \
            mma_group<N, 4, (S) == 5>(acc, xa, sd.d[S]); \
            const uint32_t ho = R + ((C) == 2 ? R_HPO : (C) * 8192) + wq * 2048 + lane * 16; \
            sched_fence(); \
            _Pragma("unroll") for (int v = ((C) == 0); v < 4; v++) { const uint32_t* h_ = hf + 16 * (C) - 4 + 4 * v; sts128(ho + (v - ((C) == 0)) * 512, h_[0], h_[1], h_[2], h_[3]); } \
            sched_fence(); \
            mma_group<N, 4, false>(acc, xa + 16, sd.d[S] + 512); \
        } while (0)
#define SHIP(C) do { \
            fence_async_smem(); __syncwarp(); \
            asm volatile("{.reg .pred p; elect.sync _|p, 0xffffffff;\n" \
                "@p cp.async.bulk.shared::cluster.shared::cta.mbarrier::complete_tx::bytes [%0], [%1], %2, [%3];}" \
                ::"r"(mapa(R + R_HPF + ((C) == 0 ? wq * 1536 : (C) * 8192 - 2048 + wq * 2048), rank ^ 1)), "r"(R + ((C) == 2 ? R_HPO : (C) * 8192) + wq * 2048), \
                  "n"((C) == 0 ? 1536 : 2048), "r"(mapa(bar_addr(sb, ((C) == 2 ? B_HXG : B_HXF) + wg), rank ^ 1)) : "memory"); \
        } while (0)
        float dq[8];
#define GELU_EPI(S) do { \
            const uint32_t bb = sb + OFF_B1 + (fcol((S) - 1, rank) + 2 * (lane & 3)) * 4; \
            if ((S) > 2) gelu_pipe<4, 0>(hf + 16 * ((S) - 2) - 4, (S) == 3 ? dq : acc + 24, bb, zero); \
            wg_wait<0>(); reg_fence<(S) == 4 ? 24 : 32>(acc); \
            mbar_arrive_if(bar_addr(sb, B_EMPTY + ((S) & 1) * 2 + 1), rel0 | rel1); mbar_arrive_if(bar_addr(sb, B_EMPTY + ((S) & 1) * 2), rel0); TSR2(); \
            if ((S) == 2) { \
                _Pragma("unroll") for (int i = 0; i < 8; i++) asm volatile("or.b32 %0, %1, %2;" : "=f"(dq[i]) : "f"(acc[24 + i]), "r"(zero)); \
                _Pragma("unroll") for (int i = 12; i < 16; i++) lds64f(bb + (i >> 1) * 32 + ((i & 1) ? zero : 0u), acc[2 * i], acc[2 * i + 1]); \
            } \
            sched_fence(); \
            gelu_pipe<12, ((S) < 4) ? 12 : 0>(hf + 16 * ((S) - 2), acc, bb, zero); \
        } while (0)

        mbar_wait(bar_addr(sb, B_V), 0);
        TSR(); sched_fence(); bar_sync(turn, 256); TSA(); wg_fence();
        mma_group<64, 8, true>(tt, xa, sd.d[0]);
        FULL(0, 0);
        mma_group<64, 8, false>(tt, xa + 32, sd.d[0] + 1024); wg_commit();
        mbar_wait(bar_addr(sb, B_V + 1), 0);
        mma_group<64, 8, false>(tt, xa + 64, sd.d[0] + 2048); wg_commit();
        REL_MID(0);
        FULL(0, 1);
        mma_group<64, 6, false>(tt, xa + 96, sd.d[0] + 3072);
        asm volatile("{.reg .pred p; setp.ne.u32 p, %0, 0; @p bar.arrive 2, 256;}" ::"r"(lead) : "memory");
        mma_group<64, 2, false>(tt, xa + 120, sd.d[0] + 3840); wg_commit();
        mbar_wait(bar_addr(sb, B_BPHI), 0);
        float sa, sb_;
        uint32_t ea[8], eb[8];
        {
            const int r = wq * 16 + (lane & 15);
            const uint32_t pa = phik_addr(R, wq, lane);
            const uint32_t va = R + R_HPO + r * 64 + (((lane >> 4) ^ ((r >> 1) & 3)) << 4);
#define VSTORE(A, v) stsm4((va ^ ((((v) & 1) << 5) | (((v) & 2) * 72))) + ((v) >> 1) * 4096, pack2(A[8 * (v)], A[8 * (v) + 1]), \
                           pack2(A[8 * (v) + 2], A[8 * (v) + 3]), pack2(A[8 * (v) + 4], A[8 * (v) + 5]), pack2(A[8 * (v) + 6], A[8 * (v) + 7]))
            uint32_t kf[16];
            if (wg == 1) {
                FULL(1, 0);
                mma_group<64, 5, true>(acc, xa, sd.d[1]); wg_commit();
                wg_wait<1>();
                reg_fence<32>(tt);
                mbar_arrive_if(bar_addr(sb, B_EMPTY + 1), rel1);
#pragma unroll
                for (int i = 0; i < 8; i++) kf[i] = pack2(tt[2 * i], tt[2 * i + 1]);
                sched_fence();
                mma_group<64, 2, false>(acc, xa + 20, sd.d[1] + 640);
#pragma unroll
                for (int i = 8; i < 16; i++) kf[i] = pack2(tt[2 * i], tt[2 * i + 1]);
                sched_fence();
                wg_fence();
                mma_group<64, 4, true>(tt, kf, sd.bphi); wg_commit();
                mma_group<64, 5, false>(acc, xa + 28, sd.d[1] + 896);
                FULL(1, 1);
                mma_group<64, 19, false>(acc, xa + 48, sd.d[1] + 1536);
                bar_arrive(1, 256); TSB();
                mma_group<64, 1, false>(acc, xa + 124, sd.d[1] + 3968); wg_commit();
                wg_wait<0>();
                reg_fence<32>(acc);
                mbar_arrive_if(bar_addr(sb, B_EMPTY + 2 + (lane & 1)), lane < 2);
                VSTORE(acc, 0); VSTORE(acc, 1); VSTORE(acc, 2); VSTORE(acc, 3);
            } else {
                TSB();
                wg_wait<0>();
                reg_fence<32>(tt);
                mbar_arrive_if(bar_addr(sb, B_EMPTY + (lane & 1)), lane < 2);
#pragma unroll
                for (int i = 0; i < 16; i++) kf[i] = pack2(tt[2 * i], tt[2 * i + 1]);
                wg_fence();
                mma_group<64, 4, true>(tt, kf, sd.bphi); wg_commit();
                wg_wait<0>();
            }
            reg_fence<32>(tt);
            TSR2();
            float sc, sd_;
            sm_exp<false, 0, 8>(tt, ea, sa);
            sched_fence();
            sm_store(ea, rcpf(sa), pa, pa ^ 16);
            sm_exp<true, 0, 8>(tt, eb, sb_);
            sched_fence();
            sm_store(eb, rcpf(sb_), pa ^ 32, pa ^ 48);
            sm_exp<false, 0, 8>(tt + 2, ea, sc);
            mbar_wait(bar_addr(sb, B_AUX), 0);
            {
                const uint32_t bb = sb + OFF_B1 + (fcol(0, rank) + 2 * (lane & 3)) * 4;
#pragma unroll
                for (int i = 0; i < 16; i++) lds64f(bb + (i >> 1) * 32 + ((i & 1) ? zero : 0u), acc[2 * i], acc[2 * i + 1]);
            }
            sm_store(ea, rcpf(sc), pa + 1024, (pa ^ 16) + 1024);
            sm_exp<true, 0, 8>(tt + 2, eb, sd_);
            if (__builtin_expect(__any_sync(0xffffffffu, !((sa + sb_) + (sc + sd_) < 1.8446744e19f)), 0)) {
                const uint32_t pb = pa + zero;
                row_redo(tt, ea, sa, eb, sb_);
                sm_store(ea, rcpf(sa), pb, pb ^ 16); sm_store(eb, rcpf(sb_), pb ^ 32, pb ^ 48);
                row_redo(tt + 2, ea, sc, eb, sd_);
                sm_store(ea, rcpf(sc), pb + 1024, (pb ^ 16) + 1024);
            }
            sm_store(eb, rcpf(sd_), (pa ^ 32) + 1024, (pa ^ 48) + 1024);
            if (wg == 0) {
                TSR(); sched_fence(); bar_sync(1, 256); TSA(); wg_fence();
                mma_group<64, 28, true>(tt, xa, sd.d[1]);
                FULL(2, 0);
                mma_group<64, 4, false>(tt, xa + 112, sd.d[1] + 3584); wg_commit();
                mma_group<64, 5, false>(acc, xa, sd.d[2]); wg_commit();
                wg_wait<1>();
                reg_fence<32>(tt);
                mbar_arrive_if(bar_addr(sb, B_EMPTY + 2 + (lane & 1)), lane < 2);
                VSTORE(tt, 0); VSTORE(tt, 1);
                sched_fence();
                mma_group<64, 3, false>(acc, xa + 20, sd.d[2] + 640);
                VSTORE(tt, 2); VSTORE(tt, 3);
                sched_fence();
                mma_group<64, 6, false>(acc, xa + 32, sd.d[2] + 1024);
                FULL(2, 1);
                mma_group<64, 8, false>(acc, xa + 56, sd.d[2] + 1792);
                fence_async_smem();
                TSD(2);
                mbar_wait(bar_addr(sb, B_FI), 0);
                float fq[32];
                const int g = lane >> 2;
                const uint32_t fo = sb + OFF_FOUT + (wq * 16 + g) * 128 + (((lane & 3) ^ g) << 4);
                wg_fence();
                mma_group<64, 4, false>(acc, xa + 88, sd.d[2] + 2816);
#pragma unroll
                for (int h = 0; h < 4; h++) wgmma_ss16(fq + 8 * h, sd.fa + 2 * h, sd.fb + 32 * h);
                wg_commit();
                mma_group<64, 5, false>(acc, xa + 104, sd.d[2] + 3328);
                bar_arrive(2, 256); TSB();
                mma_group<64, 1, false>(acc, xa + 124, sd.d[2] + 3968); wg_commit();
                wg_wait<1>();
                reg_fence<32>(fq);
                if (wq < 2) {
#pragma unroll
                    for (int i = 0; i < 4; i++)
                        sts128((fo ^ ((i >> 1) << 6)) + (i & 1) * 1024, pack2(fq[2 * i], fq[2 * i + 1]), pack2(fq[8 + 2 * i], fq[9 + 2 * i]),
                               pack2(fq[16 + 2 * i], fq[17 + 2 * i]), pack2(fq[24 + 2 * i], fq[25 + 2 * i]));
                    fence_async_smem();
                }
                mbar_arrive(bar_addr(sb, B_FO));
                wg_wait<0>();
            } else {
                const bool hi = (wq >> 1) != 0;
                float* kp = g_kv + cs * KVN + wq * 384 + lane * 4;
                fence_async_smem();
                TSR(); sched_fence(); bar_sync(2, 256); TSA();
#pragma unroll
                for (int b = 0; b < 2; b++) {
                    float k[20];
                    wg_fence();
#pragma unroll
                    for (int s = 0; s < 8; s++) {
                        const uint64_t da = sd.kva[2 * b + (s >> 2)] + (s & 3) * 128;
                        const uint64_t db = sd.kvb[2 * b + (s >> 2)] - (uint64_t)(s & 3) * ((64u << 16) - 64u);
                        if (s) wgmma_ss40<1>(k, da, db); else wgmma_ss40<0>(k, da, db);
                    }
                    wg_commit();
                    mma_group<64, 7, false>(acc, xa + 28 * b, sd.d[2] + 896 * b);
                    wg_commit();
                    wg_wait<1>();
                    reg_fence<20>(k);
                    red128(kp + b * 1536, hi ? k[8] : k[0], hi ? k[9] : k[1], hi ? k[12] : k[4], 1.f);
                    red128(kp + b * 1536 + 128, hi ? k[10] : k[2], hi ? k[11] : k[3], hi ? k[14] : k[6], 1.f);
                    red128(kp + b * 1536 + 256, hi ? k[13] : k[5], hi ? k[15] : k[7], (lane & 1) ? k[18] : k[16], 1.f);
                    sched_fence();
                }
                mbar_arrive(bar_addr(sb, B_KVP));
                asm volatile("{.reg .pred p; setp.lt.u32 p, %1, 2; @p mbarrier.arrive.relaxed.cluster.shared::cluster.b64 _, [%0];}"
                             ::"r"(mapa(bar_addr(sb, B_RX + (lane & 1)), rank ^ 1)), "r"(tid) : "memory");
                mma_group<64, 2, false>(acc, xa + 56, sd.d[2] + 1792); wg_commit();
                mma_group<64, 6, false>(acc, xa + 64, sd.d[2] + 2048); wg_commit();
                REL_MID(2);
                mma_group<64, 9, false>(acc, xa + 88, sd.d[2] + 2816);
                bar_arrive(1, 256); TSB();
                mma_group<64, 1, false>(acc, xa + 124, sd.d[2] + 3968); wg_commit();
            }
        }
        GELU_EPI(2);
        SLOT1_HEAD_ST(3, 64, 0);
        mbar_wait_cl(bar_addr(sb, B_RX + wg), 0);
        SLOT1_REST(3, 64, SHIP(0), {});
        GELU_EPI(3);
        SLOT1_HEAD_ST(4, 48, 1);
        SLOT1_REST(4, 48, SHIP(1), {});
        mbar_wait_cl(bar_addr(sb, B_RXG), 0);
        GELU_EPI(4);
        mbar_wait_cl(bar_addr(sb, B_HXF + wg), 0);
        asm volatile("{.reg .pred p; setp.eq.u32 p, %1, 0; @p mbarrier.arrive.relaxed.cluster.shared::cluster.b64 _, [%0];}"
                     ::"r"(mapa(bar_addr(sb, B_RX + wg), rank ^ 1)), "r"(tid) : "memory");
        SLOT1_HEAD_ST(5, 64, 2);
#define MOVH(a, b) _Pragma("unroll") for (int i = a; i < b; i++) asm volatile("or.b32 %0, %1, %2;" : "+r"(xa[i]) : "r"(hf[i]), "r"(zero))
        SLOT1_REST(5, 64, SHIP(2), { MOVH(0, 16); sched_fence(); });
        const int col0 = rank * 256 + pr * 64;
#define RD(S, I) sd.r[rank][(S) - 6][I]
        const uint32_t Rw = R + wq * 2048;
        uint32_t tag;
        float ac2[32];
        uint4* pp[4];
        uint32_t sw0, ol0;
        __nv_bfloat16* op;
        {
            const int ln = lane;
            const uint32_t pa = phiq_addr(R, wq, ln), own = Rw + ln * 16, prt = own + R_HPF - 2048, prt0 = own + R_HPF - wq * 512;
            const uint64_t d0 = sd.d[6], da = sd.oa[wg];
#define LDP(v) lds128((v) < 3 ? prt0 + (v) * 512 : prt + (((v) + 1) >> 2) * 8192 + (((v) + 1) & 3) * 512, xa + 32 + 4 * (v))
            LDP(0); LDP(1); LDP(2); LDP(3);
            mbar_wait(bar_addr(sb, B_RX + wg), 1);
            FULL(6, 0);
            SLOT_END(5);
            float sc, sd_;
            uint32_t ec[8], ed[8];
            sm_exp<false, 0, 8>(acc, ec, sa);
            sm_exp<true, 0, 8>(acc, ed, sb_);
            sm_exp<false, 0, 8>(acc + 2, ea, sc);
            sm_exp<true, 0, 8>(acc + 2, eb, sd_);
            if (__builtin_expect(__any_sync(0xffffffffu, !((sa + sb_) + (sc + sd_) < 1.0995116e12f)), 0)) {
                row_redo(acc, ec, sa, ed, sb_);
                row_redo(acc + 2, ea, sc, eb, sd_);
            }
            sd_ = rcpf(sd_); sb_ = rcpf(sb_);
            float oa[48];
            TSR(); sched_fence(); bar_sync(turn, 256); TSA(); wg_fence();
            mma_group<64, 4, true>(acc, xa + 32, d0 + 1024);
            sched_fence();
            sm_store_raw(ec, pa, pa ^ 16); sm_store_raw(ea, pa + 1024, (pa ^ 16) + 1024);
            sm_store(ed, sa * sb_, pa + 8192, (pa ^ 16) + 8192);
            wg_fence();
            LDP(4); LDP(5); LDP(6);
            mma_group<64, 4, false>(acc, xa, d0);
            FULL(6, 1);
            MOVH(16, 32);
            wg_fence();
            mma_group<64, 4, false>(acc, xa + 16, d0 + 512);
            mbar_wait_cl(bar_addr(sb, B_HXG + wg), 0);
            sm_store(eb, sc * sd_, pa + 9216, (pa ^ 16) + 9216);
            sched_fence();
            wg_fence();
            mma_group<64, 3, false>(acc, hf + 32, RD(6, 0));
            mbar_wait(bar_addr(sb, B_KVB), 0);
            mma_group<64, 2, false>(acc, xa + 48, d0 + 1536);
            fence_async_smem();
            LDP(7); LDP(8); LDP(9); LDP(10);
            bar_sync(3 + wg, 128);
            mma_group<64, 1, false>(acc, xa + 56, d0 + 1792);
#pragma unroll
            for (int h = 0; h < 4; h++) {
                const uint64_t db = sd.ob + 32 * h;
                wgmma_ss24<0>(oa + 12 * h, da + 2 * h, db);
                wgmma_ss24<1>(oa + 12 * h, da + 512 + 2 * h, db + 16);
            }
            wg_commit();
            bar_arrive(other, 256); TSB();
            wg_fence();
            mma_group<64, 1, false>(acc, xa + 60, d0 + 1920);
            wg_commit();
            mma_group<64, 3, false>(acc, xa + 64, RD(6, 1));
            wg_commit();
            const uint32_t rem_bar = mapa(bar_addr(sb, B_HXO + wg), rank ^ 1), rem_h = mapa(own + R_HPO, rank ^ 1);
            asm volatile("ld.shared.b32 %0, [%1];" : "=r"(tag) : "r"(bar_addr(sb, B_TAG)) : "memory");
            wg_wait<1>();
            reg_fence<48>(oa);
            mbar_arrive_if(bar_addr(sb, B_EMPTY), lane == 0);
            mbar_arrive_if(bar_addr(sb, B_HD0), rel0);
            TSD(6); TSR2();
            sched_fence();
#pragma unroll
            for (int h = 0; h < 4; h++) {
                const float* o = oa + 12 * h;
                const float r0 = rcpf(o[8]), r1 = rcpf(o[10]);
                xa[96 + 4 * h] = pack2(o[0] * r0, o[1] * r0); xa[97 + 4 * h] = pack2(o[2] * r1, o[3] * r1);
                xa[98 + 4 * h] = pack2(o[4] * r0, o[5] * r0); xa[99 + 4 * h] = pack2(o[6] * r1, o[7] * r1);
                st_async128(rem_h + h * 512, xa[96 + 4 * h], xa[97 + 4 * h], xa[98 + 4 * h], xa[99 + 4 * h], rem_bar);
            }
            wg_wait<0>();
            reg_fence<32>(acc);
            sched_fence();
            {
                const int l2 = lane + (tag >> 1);
                const uint4* pb = g_part + (size_t)((bid & ~7) | (int)rank) * 3072 + warp * 128 + l2;
#pragma unroll
                for (int j = 0; j < 4; j++) asm volatile("mov.b64 %0, %1;" : "=l"(pp[j]) : "l"(pb + ((pr + 1 + j) & 3) * 6144 + (j % 3) * 1024));
                asm volatile("mov.b32 %0, %1;" : "=r"(sw0) : "r"((l2 & 15) * 128 + (((l2 >> 4) ^ (l2 & 7)) << 4)));
                asm volatile("mov.b32 %0, %1;" : "=r"(ol0) : "r"(Rw + R_HPO + (l2 >> 3) * 128 + (((l2 & 7) ^ (l2 >> 3)) << 4)));
                asm volatile("mov.b64 %0, %1;" : "=l"(op) : "l"(out + (size_t)(row0 + (l2 >> 3)) * DM + col0 + (l2 & 7) * 8));
            }
            const uint64_t d1 = sd.d[7];
            TURN(7);
            wgmma_rs64<2>(ac2, xa, d1);
            mma_group<64, 5, false>(ac2, xa + 4, d1 + 128);
            mbar_wait_cl(bar_addr(sb, B_HXO + wg), 0);
            FULL(7, 1);
            wg_fence();
#pragma unroll
            for (int v = 0; v < 4; v++) lds128(own + R_HPO + v * 512, xa + 112 + 4 * v);
            mma_group<64, 10, false>(ac2, xa + 24, d1 + 768);
            mma_group<64, 4, false>(acc, xa + 96, RD(6, 2));
            wg_fence();
            mma_group<64, 4, false>(acc, xa + 112, RD(6, 3));
            wg_commit();
            mma_group<64, 3, false>(ac2, hf + 32, RD(7, 0));
            mma_group<64, 3, false>(ac2, xa + 64, RD(7, 1));
            wg_commit();
            wg_wait<1>();
            reg_fence<32>(acc);
            mbar_arrive_if(bar_addr(sb, B_EMPTY + 1 + (lane & 1)), lane < 2);
            TSD(7);
            mma_group<64, 4, false>(ac2, xa + 96, RD(7, 2));
            mma_group<64, 2, false>(ac2, xa + 112, RD(7, 3));
            bar_arrive(other, 256); TSB();
            mma_group<64, 2, false>(ac2, xa + 120, RD(7, 3) + 256);
            wg_commit();
            sched_fence();
            send_partial(pp[0], acc, tag);
            sched_fence();
            wg_wait<0>();
            reg_fence<32>(ac2);
            TSR2();
            send_partial(pp[1], ac2, tag);
            uint32_t xr[16], bw[8];
            mbar_wait(bar_addr(sb, B_XR), 0);
#pragma unroll
            for (int i = 0; i < 8; i++) asm volatile("ld.shared.b32 %0, [%1];" : "=r"(bw[i]) : "r"(sb + OFF_XR + 16384 + (lane & 3) * 4 + i * 16) : "memory");
#pragma unroll
            for (int v = 0; v < 4; v++) ldsm4(sb + OFF_XR + warp * 2048 + (sw0 ^ (v * 32)), xr + 4 * v);
#pragma unroll
            for (int i = 0; i < 16; i++) asm volatile("add.rn.bf16x2 %0, %0, %1;" : "+r"(xr[i]) : "r"(bw[i >> 1]));
#pragma unroll
            for (int i = 0; i < 16; i++) { acc[2 * i] = bf_lo(xr[i]); acc[2 * i + 1] = bf_hi(xr[i]); }
        }
        const uint4* const myp = pp[3];
        uint32_t pv[16], pw[16];
#define SLOT2(S, MID0, MID) do { \
            TURN(S); \
            mma_group<64, 8, false>(acc, xa, sd.d[S]); \
            MID0; \
            mma_group<64, 4, false>(acc, xa + 32, sd.d[S] + 1024); \
            FULL(S, 1); \
            mma_group<64, 4, false>(acc, xa + 48, sd.d[S] + 1536); \
            MID; \
            mma_group<64, 3, false>(acc, hf + 32, RD(S, 0)); \
            mma_group<64, 3, false>(acc, xa + 64, RD(S, 1)); \
            TSD(S); \
            mma_group<64, 4, false>(acc, xa + 96, RD(S, 2)); \
            mma_group<64, 2, false>(acc, xa + 112, RD(S, 3)); \
            if ((S) < 9) { bar_arrive(other, 256); TSB(); } \
            else asm volatile("{.reg .pred p; setp.ne.u32 p, %0, 0; @p bar.arrive 2, 256;}" ::"r"(lead) : "memory"); \
            mma_group<64, 2, false>(acc, xa + 120, RD(S, 3) + 256); wg_commit(); \
        } while (0)
#define LOADP(V, J) _Pragma("unroll") for (int i = 0; i < 4; i++) ld_poll128(myp + (J) * 1024 + i * 32, V + 4 * i)
        SLOT2(8, {}, { LOADP(pv, 0); });
        wg_wait<0>();
        reg_fence<32>(acc);
        TSR2();
        send_partial(pp[2], acc, tag);
        sched_fence();
        poll_partial(myp, pv, tag);
#pragma unroll
        for (int i = 0; i < 16; i++) { acc[2 * i] = bf_lo(pv[i]); acc[2 * i + 1] = bf_hi(pv[i]); }
        SLOT2(9, { LOADP(pw, 1); }, { LOADP(pv, 2); });
        sched_fence();
        poll_partial(myp + 1024, pw, tag);
        poll_partial(myp + 2048, pv, tag);
        float base[32];
#pragma unroll
        for (int i = 0; i < 16; i++) { base[2 * i] = bf_lo(pv[i]) + bf_lo(pw[i]); base[2 * i + 1] = bf_hi(pv[i]) + bf_hi(pw[i]); }
        sched_fence();
        TS(22);
        wg_wait<0>();
        reg_fence<32>(acc);
        TS(24);
#pragma unroll
        for (int v = 0; v < 4; v++)
            stsm4(Rw + R_HPO + (sw0 ^ (v * 32)), pack2(acc[8 * v] + base[8 * v], acc[8 * v + 1] + base[8 * v + 1]), pack2(acc[8 * v + 2] + base[8 * v + 2], acc[8 * v + 3] + base[8 * v + 3]),
                  pack2(acc[8 * v + 4] + base[8 * v + 4], acc[8 * v + 5] + base[8 * v + 5]), pack2(acc[8 * v + 6] + base[8 * v + 6], acc[8 * v + 7] + base[8 * v + 7]));
        __syncwarp();
#pragma unroll
        for (int j = 0; j < 4; j++) {
            uint32_t v[4];
            lds128((ol0 ^ ((j & 1) * 576)) + (j >> 1) * 1024, v);
            asm volatile("st.global.v4.b32 [%0], {%1,%2,%3,%4};" ::"l"(op + j * 4 * DM), "r"(v[0]), "r"(v[1]), "r"(v[2]), "r"(v[3]) : "memory");
        }
        TS(25); TSG(63);
    }
}

typedef CUresult (*EncodeFn)(CUtensorMap*, CUtensorMapDataType, cuuint32_t, void*, const cuuint64_t*, const cuuint64_t*,
                             const cuuint32_t*, const cuuint32_t*, CUtensorMapInterleave, CUtensorMapSwizzle,
                             CUtensorMapL2promotion, CUtensorMapFloatOOBfill);

static void make_map(EncodeFn enc, CUtensorMap* m, const void* p, int cols, int rows) {
    cuuint64_t gd[2] = {(cuuint64_t)cols, (cuuint64_t)rows};
    cuuint64_t gs[1] = {(cuuint64_t)cols * 2};
    cuuint32_t bx[2] = {64, 128};
    cuuint32_t es[2] = {1, 1};
    enc(m, CU_TENSOR_MAP_DATA_TYPE_BFLOAT16, 2, const_cast<void*>(p), gd, gs, bx, es, CU_TENSOR_MAP_INTERLEAVE_NONE,
        CU_TENSOR_MAP_SWIZZLE_128B, CU_TENSOR_MAP_L2_PROMOTION_L2_128B, CU_TENSOR_MAP_FLOAT_OOB_FILL_NONE);
}

extern "C" void kernel_launch(void* const* d_in, const int* in_sizes, int n_in, void* d_out, int out_size) {
    const __nv_bfloat16* x = (const __nv_bfloat16*)d_in[0];
    const __nv_bfloat16* wqkv = (const __nv_bfloat16*)d_in[1];
    const __nv_bfloat16* wphi = (const __nv_bfloat16*)d_in[2];
    const __nv_bfloat16* wo = (const __nv_bfloat16*)d_in[3];
    const __nv_bfloat16* w1 = (const __nv_bfloat16*)d_in[5];
    const __nv_bfloat16* b1 = (const __nv_bfloat16*)d_in[6];
    const __nv_bfloat16* w2 = (const __nv_bfloat16*)d_in[7];
    const __nv_bfloat16* b2 = (const __nv_bfloat16*)d_in[8];

    static EncodeFn enc = nullptr;
    if (!enc) {
        void* fn = nullptr;
        cudaDriverEntryPointQueryResult qr;
        cudaGetDriverEntryPoint("cuTensorMapEncodeTiled", &fn, cudaEnableDefault, &qr);
        enc = (EncodeFn)fn;
        cudaFuncSetAttribute(fused_hedgehog_gelu_kernel, cudaFuncAttributeMaxDynamicSharedMemorySize, SMEM_BYTES);
    }
    CUtensorMap m_x;
    {
        cuuint64_t gd[3] = {64, 2048, 8};
        cuuint64_t gs[2] = {1024, 128};
        cuuint32_t bx[3] = {64, 64, 2};
        cuuint32_t es[3] = {1, 1, 1};
        enc(&m_x, CU_TENSOR_MAP_DATA_TYPE_BFLOAT16, 3, const_cast<__nv_bfloat16*>(x), gd, gs, bx, es, CU_TENSOR_MAP_INTERLEAVE_NONE,
            CU_TENSOR_MAP_SWIZZLE_128B, CU_TENSOR_MAP_L2_PROMOTION_L2_256B, CU_TENSOR_MAP_FLOAT_OOB_FILL_NONE);
    }
    CUtensorMap m_x2;
    make_map(enc, &m_x2, x, DM, 2048);
    CUtensorMap m_wqkv, m_w1, m_w2, m_wo;
    make_map(enc, &m_wqkv, wqkv, 1536, DM);
    make_map(enc, &m_w1, w1, FF, DM);
    make_map(enc, &m_w2, w2, DM, FF);
    make_map(enc, &m_wo, wo, DM, DM);

    SlotDesc sd;
    const uint64_t dbase = (uint64_t)(SMEM_BASE >> 4) | (1ull << 16) | (64ull << 32) | (1ull << 62);
    for (int i = 0; i < 9; i++) sd.d[i] = dbase + ((OFF_RING + (i & 1) * 65536) >> 4);
    sd.d[9] = dbase + ((OFF_RING + 32768) >> 4);
    for (int rk = 0; rk < 2; rk++)
        for (int i = 0; i < 4; i++) {
            const uint32_t c = (i == 2) ? OFF_REG + R_PHI : (i == 3) ? OFF_RING + 65536 : OFF_RING + i * 65536 + 32768;
            const uint32_t o = (i == 2) ? OFF_REG + RSTEP + R_PHI : c + 16384;
            sd.r[rk][i][0] = dbase + ((c + rk * 6144) >> 4);       sd.r[rk][i][1] = dbase + ((c + (rk ^ 1) * 6144) >> 4);
            sd.r[rk][i][2] = dbase + ((o + rk * 8192) >> 4);       sd.r[rk][i][3] = dbase + ((o + (rk ^ 1) * 8192) >> 4);
        }
    sd.bphi = dbase + (OFF_BPHI >> 4);
    for (int i = 0; i < 4; i++) {
        const uint32_t vo = OFF_REG + (i & 1) * RSTEP + R_HPO + (i >> 1) * 4096;
        sd.kva[i] = dbase + ((OFF_REG + (i & 1) * RSTEP + R_PHI + (i >> 1) * 8192) >> 4);
        sd.kvb[i] = (uint64_t)((SMEM_BASE + vo) >> 4) | ((uint64_t)((OFF_ONES - vo) >> 4) << 16) | (32ull << 32) | (2ull << 62);
    }
    sd.fa = dbase + (OFF_FIN >> 4);
    sd.fb = (uint64_t)((SMEM_BASE + OFF_FIN + 4096) >> 4) | (1ull << 16) | (16ull << 32) | (3ull << 62);
    sd.oa[0] = dbase + ((OFF_REG + RSTEP + R_PHI) >> 4);   sd.oa[1] = dbase + ((OFF_REG + R_PHI) >> 4);
    sd.ob = (uint64_t)((SMEM_BASE + OFF_KVB) >> 4) | (8ull << 16) | ((uint64_t)(RSTEP >> 4) << 32);
    cudaLaunchConfig_t cfg = {};
    cfg.gridDim = dim3(NCTA);
    cfg.blockDim = dim3(NTHREADS);
    cfg.dynamicSmemBytes = SMEM_BYTES;
    cfg.stream = cudaStreamPerThread;
    cudaLaunchAttribute at[1];
    at[0].id = cudaLaunchAttributeClusterDimension;
    at[0].val.clusterDim.x = 2; at[0].val.clusterDim.y = 1; at[0].val.clusterDim.z = 1;
    cfg.attrs = at; cfg.numAttrs = 1;
    cudaLaunchKernelEx(&cfg, fused_hedgehog_gelu_kernel, m_x, m_x2, m_wqkv, m_w1, m_w2, m_wo, wqkv, wphi, wo, w1, b1, w2, b2,
                       (__nv_bfloat16*)d_out, sd);
}
```
